```python
import torch

def _softmax(x, axis=-1):
    return torch.softmax(x, dim=axis)

def _gelu(x):
    return torch.nn.functional.gelu(x, approximate='tanh')

def _silu(x):
    return torch.nn.functional.silu(x)

def _sigmoid(x):
    return torch.sigmoid(x)

def _layernorm(x, axis=-1, eps=1e-05):
    m = x.mean(dim=axis, keepdim=True)
    v = x.var(dim=axis, keepdim=True, unbiased=False)
    return (x - m) / torch.sqrt(v + eps)

def _scatter_add(tgt, idx, src, axis=0):
    return tgt.clone().index_add_(axis, idx, src)

def _segment_sum(src, seg, n):
    out = torch.zeros((n,) + src.shape[1:], dtype=src.dtype)
    return out.index_add_(0, seg, src)

def _pad(x, pw):
    flat = tuple((v for pair in reversed(pw) for v in pair))
    return torch.nn.functional.pad(x, flat)
kernel_name = 'standalone__factorization_afm__recsys'

def setup_inputs():

    _w = lambda a: (lambda t: t.to(torch.bfloat16) if t.is_floating_point() else t)(torch.as_tensor(a))
    B, F, D, V = (1024, 26, 128, min(1000000, 100000))
    A = D
    ii, jj = tuple(torch.triu_indices(F, F, 1).unbind(0))
    return {'idx': _w((lambda lo, hi, *s: torch.randint(lo, hi, s))(0, V, B, F).to(torch.int64)), 'table': _w((lambda *s: torch.randn(*s, dtype=torch.bfloat16) * 0.8)(V, D)), 'ii': _w(ii.to(torch.int64)), 'jj': _w(jj.to(torch.int64)), 'W': _w((lambda *s: torch.randn(*s, dtype=torch.bfloat16) * 0.4)(D, A) * (1.0 / D ** 0.5)), 'b': _w((lambda *s: torch.randn(*s, dtype=torch.bfloat16) * 0.4)(A)), 'h': _w((lambda *s: torch.randn(*s, dtype=torch.bfloat16) * 0.4)(A)), 'p': _w((lambda *s: torch.randn(*s, dtype=torch.bfloat16) * 0.8)(D))}

def reference(idx, table, ii, jj, W, b, h, p):
    emb = table[idx]
    ei = emb[:, ii, :].clone()
    ej = emb[:, jj, :].clone()
    pair = ei * ej
    hid = pair @ W + b
    hid = 0.5 * (hid + torch.abs(hid))
    e = hid @ h
    alpha = _softmax(e, axis=-1)
    pooled = torch.einsum('bp,bpd->bd', alpha, pair)
    return pooled @ p
```

```cpp
#include <cuda_runtime.h>
#include <cuda_bf16.h>
#include <cuda_fp16.h>
#include <stdint.h>
#include <type_traits>

#define AFM_R2POS 0
#define AFM_TURNS 1
namespace {

constexpr int kF = 26;
constexpr int kD = 128;
constexpr int kP = 325;
constexpr int kMaxB = 8;
constexpr int kThreads = 256;
constexpr int kRow = 320;
constexpr int kElem = kF * kRow;

constexpr int B_NBLK = 16 * 1024;
constexpr int OFF_B = 0;
constexpr int OFF_EMB = 2 * B_NBLK;
constexpr int OFF_ES = OFF_EMB + kMaxB * kElem;
constexpr int ES_STRIDE = 328 * 4;
constexpr int OFF_VEC = OFF_ES + (kMaxB + 1) * ES_STRIDE;
constexpr int OFF_STAT = OFF_VEC + 768;
constexpr int OFF_BAR = OFF_STAT + 96;
constexpr int OFF_WRAW = OFF_BAR + 128;
constexpr int SMEM_USED = OFF_WRAW + kD * kD * 2;
constexpr int SMEM_BYTES = SMEM_USED;
static_assert(OFF_ES % 16 == 0 && OFF_VEC % 16 == 0 && OFF_STAT % 16 == 0 && OFF_WRAW % 128 == 0 && kElem % 128 == 0, "alignment");

struct Sched { uint32_t e[32]; };

__device__ __forceinline__ uint32_t smem_u32(const void* p) { return (uint32_t)__cvta_generic_to_shared(p); }
__device__ __forceinline__ void named_bar_sync(int id, int n) { asm volatile("bar.sync %0, %1;" ::"r"(id), "r"(n) : "memory"); }
__device__ __forceinline__ void named_bar_arrive(int id, int n) { asm volatile("bar.arrive %0, %1;" ::"r"(id), "r"(n) : "memory"); }
__device__ __forceinline__ void mbar_wait(uint32_t bar, uint32_t parity) {
  uint32_t ok, it = 0;
  do {
    asm volatile("{\n.reg .pred p;\nmbarrier.try_wait.parity.shared::cta.b64 p, [%1], %2;\nselp.u32 %0, 1, 0, p;\n}\n"
                 : "=r"(ok) : "r"(bar), "r"(parity) : "memory");
  } while (!ok && ++it < (1u << 20));
}
__device__ __forceinline__ void wgmma_fence() { asm volatile("wgmma.fence.sync.aligned;" ::: "memory"); }
__device__ __forceinline__ void wgmma_commit() { asm volatile("wgmma.commit_group.sync.aligned;" ::: "memory"); }
template <int N>
__device__ __forceinline__ void wgmma_wait() { asm volatile("wgmma.wait_group.sync.aligned %0;" ::"n"(N) : "memory"); }
__device__ __forceinline__ void fence_proxy_async() { asm volatile("fence.proxy.async.shared::cta;" ::: "memory"); }

__device__ __forceinline__ uint32_t hmul2(uint32_t a, uint32_t b) {
  uint32_t d;
  asm("mul.rn.f16x2 %0, %1, %2;" : "=r"(d) : "r"(a), "r"(b));
  return d;
}
__device__ __forceinline__ uint32_t hadd2(uint32_t a, uint32_t b) {
  uint32_t d;
  asm("add.rn.f16x2 %0, %1, %2;" : "=r"(d) : "r"(a), "r"(b));
  return d;
}
__device__ __forceinline__ uint32_t hfma2(uint32_t a, uint32_t b, uint32_t c) {
  uint32_t d;
  asm("fma.rn.f16x2 %0, %1, %2, %3;" : "=r"(d) : "r"(a), "r"(b), "r"(c));
  return d;
}
__device__ __forceinline__ uint32_t bias_relu2(uint32_t x, uint32_t b) {
  uint32_t d;
  asm("fma.rn.relu.f16x2 %0, %1, %2, %3;" : "=r"(d) : "r"(x), "r"(0x3C003C00u), "r"(b));
  return d;
}
__device__ __forceinline__ uint32_t habsmax2(uint32_t a, uint32_t b) {
  uint32_t d;
  asm("max.NaN.xorsign.abs.f16x2 %0, %1, %2;" : "=r"(d) : "r"(a), "r"(b));
  return d;
}
__device__ __forceinline__ uint32_t hmax2(uint32_t a, uint32_t b) {
  uint32_t d;
  asm("max.f16x2 %0, %1, %2;" : "=r"(d) : "r"(a), "r"(b));
  return d;
}
__device__ __forceinline__ uint32_t bf2h(uint32_t x) {
  uint32_t d;
  asm("cvt.rn.f16x2.f32 %0, %1, %2;" : "=r"(d) : "f"(__uint_as_float(x & 0xffff0000u)), "f"(__uint_as_float(x << 16)));
  return d;
}
__device__ __forceinline__ uint32_t bf2h_x16(uint32_t x) {
  uint32_t y;
  asm("mul.rn.bf16x2 %0, %1, %2;" : "=r"(y) : "r"(x), "r"(0x41804180u));
  return bf2h(y);
}
__device__ __forceinline__ float h_lo(uint32_t x) { return __half2float(__ushort_as_half((unsigned short)(x & 0xffffu))); }
__device__ __forceinline__ float h_hi(uint32_t x) { return __half2float(__ushort_as_half((unsigned short)(x >> 16))); }
__device__ __forceinline__ uint32_t redux_max(uint32_t v) {
  uint32_t d;
  asm volatile("redux.sync.max.u32 %0, %1, 0xffffffff;" : "=r"(d) : "r"(v));
  return d;
}
__device__ __forceinline__ uint32_t absmax_bits(uint32_t m) { return max(m & 0x7fffu, (m >> 16) & 0x7fffu); }

template <int OFF>
__device__ __forceinline__ uint4 lds128(uint32_t addr) {
  uint4 v;
  asm volatile("ld.shared.v4.u32 {%0,%1,%2,%3}, [%4+%5];" : "=r"(v.x), "=r"(v.y), "=r"(v.z), "=r"(v.w) : "r"(addr), "n"(OFF));
  return v;
}
template <int OFF>
__device__ __forceinline__ void sts128(uint32_t addr, uint4 v) {
  asm volatile("st.shared.v4.u32 [%0+%5], {%1,%2,%3,%4};" ::"r"(addr), "r"(v.x), "r"(v.y), "r"(v.z), "r"(v.w), "n"(OFF) : "memory");
}
__device__ __forceinline__ void sts32(uint32_t addr, uint32_t v) { asm volatile("st.shared.u32 [%0], %1;" ::"r"(addr), "r"(v) : "memory"); }
__device__ __forceinline__ uint32_t ldg32(const void* p) {
  uint32_t v;
  asm volatile("ld.global.u32 %0, [%1];" : "=r"(v) : "l"(p) : "memory");
  return v;
}
__device__ __forceinline__ uint4 ldg128(const void* p) {
  uint4 v;
  asm volatile("ld.global.nc.v4.u32 {%0,%1,%2,%3}, [%4];" : "=r"(v.x), "=r"(v.y), "=r"(v.z), "=r"(v.w) : "l"(p));
  return v;
}
__device__ __forceinline__ uint2 ldg64(const void* p) {
  uint2 v;
  asm volatile("ld.global.v2.u32 {%0,%1}, [%2];" : "=r"(v.x), "=r"(v.y) : "l"(p) : "memory");
  return v;
}
__device__ __forceinline__ uint4 ldg128p(const void* p, bool on) {
  uint4 v = make_uint4(0u, 0u, 0u, 0u);
  asm volatile("{\n.reg .pred p;\nsetp.ne.u32 p, %5, 0;\n@p ld.global.v4.u32 {%0,%1,%2,%3}, [%4];\n}"
               : "+r"(v.x), "+r"(v.y), "+r"(v.z), "+r"(v.w) : "l"(p), "r"((uint32_t)on) : "memory");
  return v;
}
template <int OFF>
__device__ __forceinline__ uint4 lds128p(uint32_t addr, bool on) {
  uint4 v;
  asm volatile("{\n.reg .pred p;\nsetp.ne.u32 p, %6, 0;\n@p ld.shared.v4.u32 {%0,%1,%2,%3}, [%4+%5];\n}"
               : "=r"(v.x), "=r"(v.y), "=r"(v.z), "=r"(v.w) : "r"(addr), "n"(OFF), "r"((uint32_t)on));
  return v;
}
template <int OFF>
__device__ __forceinline__ void sts128p(uint32_t addr, uint4 v, bool on) {
  asm volatile("{\n.reg .pred p;\nsetp.ne.u32 p, %6, 0;\n@p st.shared.v4.u32 [%0+%5], {%1,%2,%3,%4};\n}"
               ::"r"(addr), "r"(v.x), "r"(v.y), "r"(v.z), "r"(v.w), "n"(OFF), "r"((uint32_t)on) : "memory");
}
__device__ __forceinline__ void sts32p(uint32_t addr, uint32_t v, bool on) {
  asm volatile("{\n.reg .pred p;\nsetp.ne.u32 p, %2, 0;\n@p st.shared.u32 [%0], %1;\n}" ::"r"(addr), "r"(v), "r"((uint32_t)on) : "memory");
}
__device__ __forceinline__ void pin2(uint32_t a, uint32_t b, uint32_t never) {
  asm volatile("{\n.reg .pred p;\nsetp.ne.u32 p, %2, 0;\n@p st.shared.u32 [%0], %1;\n}" ::"r"(a), "r"(b), "r"(never) : "memory");
}
template <int M>
__device__ __forceinline__ uint32_t shfl_xor(uint32_t v) {
  uint32_t d;
  asm volatile("shfl.sync.bfly.b32 %0, %1, %2, 0x1f, 0xffffffff;" : "=r"(d) : "r"(v), "n"(M));
  return d;
}
template <int I, int N, typename F>
__device__ __forceinline__ void static_for(F&& f) {
  if constexpr (I < N) {
    f(std::integral_constant<int, I>{});
    static_for<I + 1, N>(f);
  }
}
template <int N>
__device__ __forceinline__ void fence_regs(uint32_t (&r)[N]) {
#pragma unroll
  for (int i = 0; i < N; i++) asm volatile("" : "+r"(r[i])::"memory");
}
__device__ __forceinline__ void load_vec(uint32_t (&v)[16], uint32_t a) {
  const uint4 v0 = lds128<0>(a), v1 = lds128<64>(a), v2 = lds128<128>(a), v3 = lds128<192>(a);
  v[0] = v0.x; v[1] = v0.y; v[2] = v0.z; v[3] = v0.w; v[4] = v1.x; v[5] = v1.y; v[6] = v1.z; v[7] = v1.w;
  v[8] = v2.x; v[9] = v2.y; v[10] = v2.z; v[11] = v2.w; v[12] = v3.x; v[13] = v3.y; v[14] = v3.z; v[15] = v3.w;
}

__device__ __forceinline__ void sched_fence(uint32_t& ck, uint32_t never) {
  asm volatile("{\n.reg .pred p;\nsetp.ne.u32 p, %1, 0;\n@p mov.u32 %0, %%clock;\n}" : "+r"(ck) : "r"(never) : "memory");
}

template <int ACCUM>
__device__ __forceinline__ void wgmma_rs_n128(uint32_t (&d)[32], uint32_t a0, uint32_t a1, uint32_t a2, uint32_t a3, uint64_t descB) {
  if (ACCUM == 1) {
    asm volatile(
        "wgmma.mma_async.sync.aligned.m64n128k16.f16.f16.f16 "
        "{%0, %1, %2, %3, %4, %5, %6, %7, %8, %9, %10, %11, %12, %13, %14, %15, %16, %17, %18, %19, %20, %21, %22, %23, %24, %25, %26, %27, %28, %29, %30, %31}, "
        "{%32, %33, %34, %35}, %36, 1, 1, 1, 1;\n"
        : "+r"(d[0]), "+r"(d[1]), "+r"(d[2]), "+r"(d[3]), "+r"(d[4]), "+r"(d[5]), "+r"(d[6]), "+r"(d[7]), "+r"(d[8]), "+r"(d[9]), "+r"(d[10]), "+r"(d[11]), "+r"(d[12]), "+r"(d[13]), "+r"(d[14]), "+r"(d[15]), "+r"(d[16]), "+r"(d[17]), "+r"(d[18]), "+r"(d[19]), "+r"(d[20]), "+r"(d[21]), "+r"(d[22]), "+r"(d[23]), "+r"(d[24]), "+r"(d[25]), "+r"(d[26]), "+r"(d[27]), "+r"(d[28]), "+r"(d[29]), "+r"(d[30]), "+r"(d[31])
        : "r"(a0), "r"(a1), "r"(a2), "r"(a3), "l"(descB));
  }
  if (ACCUM == 0) {
    asm volatile(
        "wgmma.mma_async.sync.aligned.m64n128k16.f16.f16.f16 "
        "{%0, %1, %2, %3, %4, %5, %6, %7, %8, %9, %10, %11, %12, %13, %14, %15, %16, %17, %18, %19, %20, %21, %22, %23, %24, %25, %26, %27, %28, %29, %30, %31}, "
        "{%32, %33, %34, %35}, %36, 0, 1, 1, 1;\n"
        : "=r"(d[0]), "=r"(d[1]), "=r"(d[2]), "=r"(d[3]), "=r"(d[4]), "=r"(d[5]), "=r"(d[6]), "=r"(d[7]), "=r"(d[8]), "=r"(d[9]), "=r"(d[10]), "=r"(d[11]), "=r"(d[12]), "=r"(d[13]), "=r"(d[14]), "=r"(d[15]), "=r"(d[16]), "=r"(d[17]), "=r"(d[18]), "=r"(d[19]), "=r"(d[20]), "=r"(d[21]), "=r"(d[22]), "=r"(d[23]), "=r"(d[24]), "=r"(d[25]), "=r"(d[26]), "=r"(d[27]), "=r"(d[28]), "=r"(d[29]), "=r"(d[30]), "=r"(d[31])
        : "r"(a0), "r"(a1), "r"(a2), "r"(a3), "l"(descB));
  }
}
__device__ __forceinline__ void wgmma_rs_n128_p(uint32_t (&d)[32], uint32_t a0, uint32_t a1, uint32_t a2, uint32_t a3, uint64_t descB, uint32_t accum) {
  asm volatile(
      "{\n.reg .pred p;\nsetp.ne.u32 p, %37, 0;\n"
      "wgmma.mma_async.sync.aligned.m64n128k16.f16.f16.f16 "
      "{%0, %1, %2, %3, %4, %5, %6, %7, %8, %9, %10, %11, %12, %13, %14, %15, %16, %17, %18, %19, %20, %21, %22, %23, %24, %25, %26, %27, %28, %29, %30, %31}, "
      "{%32, %33, %34, %35}, %36, p, 1, 1, 1;\n}\n"
      : "+r"(d[0]), "+r"(d[1]), "+r"(d[2]), "+r"(d[3]), "+r"(d[4]), "+r"(d[5]), "+r"(d[6]), "+r"(d[7]), "+r"(d[8]), "+r"(d[9]), "+r"(d[10]), "+r"(d[11]), "+r"(d[12]), "+r"(d[13]), "+r"(d[14]), "+r"(d[15]), "+r"(d[16]), "+r"(d[17]), "+r"(d[18]), "+r"(d[19]), "+r"(d[20]), "+r"(d[21]), "+r"(d[22]), "+r"(d[23]), "+r"(d[24]), "+r"(d[25]), "+r"(d[26]), "+r"(d[27]), "+r"(d[28]), "+r"(d[29]), "+r"(d[30]), "+r"(d[31])
      : "r"(a0), "r"(a1), "r"(a2), "r"(a3), "l"(descB), "r"(accum));
}

#define TL(slot)
#define TLL(off) sched_fence(ck, never)
#define TLX(off)
#define TLS()

__device__ __forceinline__ float rbf(float x) { return __bfloat162float(__float2bfloat16_rn(x)); }
__device__ __forceinline__ float warp_sum(float v) {
#pragma unroll
  for (int o = 16; o > 0; o >>= 1) v += __shfl_xor_sync(0xffffffffu, v, o);
  return v;
}

__device__ __noinline__ void general_element(const int* __restrict__ idx, const __nv_bfloat16* __restrict__ table,
                                             const int* __restrict__ ii, const int* __restrict__ jj,
                                             const __nv_bfloat16* __restrict__ W, const __nv_bfloat16* __restrict__ bias,
                                             const __nv_bfloat16* __restrict__ hvec, const __nv_bfloat16* __restrict__ pvec,
                                             __nv_bfloat16* __restrict__ out, float* ev) {
  const int lane = threadIdx.x & 31;
  auto pair4 = [&](int p, float (&pr)[4]) {
    const __nv_bfloat16* a = table + (size_t)idx[ii[p]] * kD + 4 * lane;
    const __nv_bfloat16* b = table + (size_t)idx[jj[p]] * kD + 4 * lane;
#pragma unroll
    for (int q = 0; q < 4; q++) pr[q] = rbf(__bfloat162float(a[q]) * __bfloat162float(b[q]));
  };
  float m = -INFINITY;
  bool has_nan = false;
  for (int p = 0; p < kP; p++) {
    float pr[4], x[4] = {0.f, 0.f, 0.f, 0.f};
    pair4(p, pr);
    for (int l = 0; l < 32; l++) {
#pragma unroll
      for (int q = 0; q < 4; q++) {
        const float v = __shfl_sync(0xffffffffu, pr[q], l);
        const uint2 w = *reinterpret_cast<const uint2*>(W + (4 * l + q) * kD + 4 * lane);
        x[0] = fmaf(v, __uint_as_float(w.x << 16), x[0]);
        x[1] = fmaf(v, __uint_as_float(w.x & 0xffff0000u), x[1]);
        x[2] = fmaf(v, __uint_as_float(w.y << 16), x[2]);
        x[3] = fmaf(v, __uint_as_float(w.y & 0xffff0000u), x[3]);
      }
    }
    float e = 0.f;
#pragma unroll
    for (int q = 0; q < 4; q++) {
      const float y = rbf(rbf(x[q]) + __bfloat162float(bias[4 * lane + q]));
      e = fmaf(rbf(0.5f * rbf(y + fabsf(y))), __bfloat162float(hvec[4 * lane + q]), e);
    }
    e = rbf(warp_sum(e));
    has_nan |= (e != e);
    m = fmaxf(m, e);
    if (lane == 0) ev[p] = e;
  }
  __syncwarp();
  float l = 0.f;
  for (int p = lane; p < kP; p += 32) l += expf(ev[p] - m);
  l = warp_sum(l);
  float pooled[4] = {0.f, 0.f, 0.f, 0.f};
  for (int p = 0; p < kP; p++) {
    float pr[4];
    pair4(p, pr);
    const float al = rbf(expf(ev[p] - m) / l);
#pragma unroll
    for (int q = 0; q < 4; q++) pooled[q] = fmaf(al, pr[q], pooled[q]);
  }
  float o = 0.f;
#pragma unroll
  for (int q = 0; q < 4; q++) o = fmaf(rbf(pooled[q]), __bfloat162float(pvec[4 * lane + q]), o);
  o = warp_sum(o);
  if (has_nan) o = __int_as_float(0x7fffffff);
  if (lane == 0) *out = __float2bfloat16_rn(o);
}

__global__ void __launch_bounds__(kThreads, 1)
afm_kernel(const int* __restrict__ idx, const __nv_bfloat16* __restrict__ table,
           const int* __restrict__ ii, const int* __restrict__ jj,
           const __nv_bfloat16* __restrict__ W, const __nv_bfloat16* __restrict__ bias,
           const __nv_bfloat16* __restrict__ hvec, const __nv_bfloat16* __restrict__ pvec,
           __nv_bfloat16* __restrict__ out, int base_cnt, int extra, int last_row,
           const __grid_constant__ Sched sched) {
  extern __shared__ __align__(1024) uint8_t smem[];
  constexpr uint32_t sbase = 0x400u;

  const int tid = threadIdx.x;
  const int t = tid & 127;
  const int lane = tid & 31;
  const int warp = tid >> 5;
  const int c = lane & 3;
  const int tau = t >> 2;
  TL(0);
  const int cta = blockIdx.x;
  const int b0 = cta * base_cnt + min(cta, extra);

  const int grp = 7 - (t >> 4);
  int irow = (b0 + (tid >> 7)) * kF + 4 * grp;
  uint32_t gi[2][4];
  auto load_idx = [&](int j) {
    const uint2 lo = ldg64(idx + min(irow, last_row));
    const uint2 hi = ldg64(idx + min(irow + 2, last_row));
    gi[j][0] = lo.x; gi[j][1] = lo.y; gi[j][2] = hi.x; gi[j][3] = hi.y;
    irow += 2 * kF;
  };
  load_idx(0);
  const uint32_t wbar = sbase + OFF_BAR + warp * 8;
  if (lane == 0) {
    asm volatile("mbarrier.init.shared::cta.b64 [%0], 1;\n"
                 "fence.mbarrier_init.release.cluster;\n"
                 "mbarrier.arrive.expect_tx.shared::cta.b64 _, [%0], 4096;\n"
                 "cp.async.bulk.shared::cluster.global.mbarrier::complete_tx::bytes [%1], [%2], 4096, [%0];"
                 ::"r"(wbar), "r"(sbase + OFF_WRAW + warp * 4096), "l"(W + warp * 16 * kD) : "memory");
  }
  const uint32_t sv = ldg32((tid < 64 ? bias : tid < 128 ? hvec : pvec) + 2 * (tid & 63));
  const uint32_t i0 = ldg32(ii + tid), j0 = ldg32(jj + tid);
  const uint32_t i1 = ldg32(ii + min(tid + 256, kP - 1)), j1 = ldg32(jj + min(tid + 256, kP - 1));
  const int wg = __shfl_sync(0xffffffffu, tid >> 7, 0);
  const int n_out = base_cnt + (cta < extra ? 1 : 0);
  const int n_c = max(n_out, 2);
  const int nb = (n_c - wg + 1) >> 1;
  const bool v01 = grp < 7, v23 = grp < 6;
  const __nv_bfloat16* gsrc = table + shfl_xor<0>((t & 15) * 8);
  uint4 g0[4];
  TL(1);
  if (wg == 1) mbar_wait(wbar, 0);
#pragma unroll
  for (int u = 0; u < 4; u++) g0[u] = ldg128p(gsrc + (size_t)gi[0][u] * kD, u < 2 ? v01 : v23);
  TL(2);
  load_idx(1);
  {
    const uint32_t sh = bf2h_x16(sv);
    const uint32_t vpos = tid < 128 ? ((tid & 112u) | ((tid & 3u) << 2) | ((tid >> 2) & 3u)) : tid;
    sts32p(sbase + OFF_VEC + vpos * 4, sh, tid < 192);
    const float vs = warp_sum(fabsf(h_lo(sh)) + fabsf(h_hi(sh)));
    uint32_t mw = 0;
    sts32p(sbase + OFF_STAT + 64 + warp * 4, __float_as_uint(vs), lane == 0);

    mbar_wait(wbar, 0);
    const uint32_t rr0 = 4 * (warp & 1) + (lane >> 4);
    const uint32_t wa = sbase + OFF_B + ((lane >> 3) & 1) * B_NBLK + (warp >> 1) * 4096 + rr0 * 128;
    const uint32_t wa0 = wa + (((lane & 7) ^ rr0) << 4), wa1 = wa + 256 + (((lane & 7) ^ (rr0 + 2)) << 4);
    const uint32_t wsrc = sbase + OFF_WRAW + warp * 4096 + lane * 16;
    uint4 wr[8];
    static_for<0, 8>([&](auto Rc) { wr[decltype(Rc)::value] = lds128<decltype(Rc)::value * 512>(wsrc); });
    static_for<0, 8>([&](auto Rc) {
      constexpr int r = decltype(Rc)::value;
      uint4 v;
      v.x = bf2h_x16(wr[r].x); v.y = bf2h_x16(wr[r].y); v.z = bf2h_x16(wr[r].z); v.w = bf2h_x16(wr[r].w);
      mw = habsmax2(habsmax2(mw, v.x), habsmax2(v.y, habsmax2(v.z, v.w)));
      sts128<(r & 3) * 1024>(r < 4 ? wa0 : wa1, v);
    });
    fence_proxy_async();
    const bool ok0 = i0 < j0 && j0 < kF && ((i0 * (2 * kF - 1 - i0)) >> 1) + j0 - i0 - 1 == tid;
    const bool ok1 = i1 < j1 && j1 < kF && ((i1 * (2 * kF - 1 - i1)) >> 1) + j1 - i1 - 1 == min(tid + 256, kP - 1);
    mw = redux_max(ok0 && ok1 ? absmax_bits(mw) : 0x7fffu);
    sts32p(sbase + OFF_STAT + warp * 4, mw, lane == 0);
  }
  const uint32_t sc = sched.e[tau];
  if (smem_u32(smem) != sbase) __trap();
  __syncthreads();
  TL(3);
  uint32_t bs[16], hs[16], ps[16];
  load_vec(bs, sbase + OFF_VEC + c * 16);
  load_vec(hs, sbase + OFF_VEC + 256 + c * 16);
  load_vec(ps, sbase + OFF_VEC + 512 + c * 16);

  uint32_t me = 0;
  uint32_t cv_ptr = sbase + OFF_EMB + wg * kElem + 4 * grp * kRow + (t & 15) * 16;
  auto convert = [&](uint4 v) {
    v.x = bf2h(v.x); v.y = bf2h(v.y); v.z = bf2h(v.z); v.w = bf2h(v.w);
    me = habsmax2(habsmax2(me, v.x), habsmax2(v.y, habsmax2(v.z, v.w)));
    return v;
  };
  sts128p<0>(cv_ptr, convert(g0[0]), v01);
  sts128p<kRow>(cv_ptr, convert(g0[1]), v01);
  sts128p<2 * kRow>(cv_ptr, convert(g0[2]), v23);
  sts128p<3 * kRow>(cv_ptr, convert(g0[3]), v23);
  const bool has_left = ((n_c & 1) == wg);
  named_bar_sync(1 + wg, 128);
  TL(4);

  uint32_t Af[32], acc[32], S0[16], S1[16], S2[16], S3[16];
  uint32_t ra[6];
#pragma unroll
  for (int r = 0; r < 6; r++) ra[r] = sbase + OFF_EMB + wg * kElem + c * 16 + ((sc >> (5 * r)) & 31u) * kRow;
  load_vec(S3, ra[5]);
  load_vec(S0, ra[0]);
  load_vec(S1, ra[1]);
  const uint32_t fl = shfl_xor<0>((c & 1) | (c < 2 ? 2u : 0u) | (v01 ? 4u : 0u) | (v23 ? 8u : 0u));
  uint32_t ck = 0;
  const uint32_t never = fl >> 31;
  const uint32_t bar_wg = 1 + wg;
  constexpr uint64_t dB = (uint64_t)(((sbase + OFF_B) & 0x3FFFFu) >> 4) | ((uint64_t)(B_NBLK >> 4) << 16) |
                          ((uint64_t)(1024 >> 4) << 32) | ((uint64_t)1 << 62);
  auto products = [&](const uint32_t (&X)[16], const uint32_t (&Y)[16], const uint32_t (&Z)[16]) {
#pragma unroll
    for (int i = 0; i < 16; i++) {
      Af[2 * i] = hmul2(X[i], Z[i]);
      Af[2 * i + 1] = hmul2(Y[i], Z[i]);
    }
  };
  auto issue = [&]() {
    fence_regs(Af);
    wgmma_fence();
#pragma unroll
    for (int s = 0; s < 8; s++) {
      const uint64_t d = dB + (uint64_t)(s * (2048 >> 4));
      if (s == 0) wgmma_rs_n128<0>(acc, Af[0], Af[1], Af[2], Af[3], d);
      else wgmma_rs_n128<1>(acc, Af[4 * s], Af[4 * s + 1], Af[4 * s + 2], Af[4 * s + 3], d);
    }
    wgmma_commit();
    named_bar_arrive(6 - bar_wg, 256);
  };
  auto gather_raw = [&](bool on) {
    static_for<0, 4>([&](auto Uc) {
      constexpr int u = decltype(Uc)::value;
      const __nv_bfloat16* src = gsrc + (size_t)gi[1][u] * kD;
      asm volatile("{\n.reg .pred p;\nsetp.ne.u32 p, %2, 0;\n@p cp.async.cg.shared.global [%0+%3], [%1], 16;\n}\n"
                   ::"r"(cv_ptr), "l"(src), "r"((uint32_t)(on && (fl & (u < 2 ? 4u : 8u)))), "n"(2 * kElem + u * kRow) : "memory");
    });
  };
#pragma unroll
  for (int i = 0; i < 16; i++) S2[i] = 0;
  products(S0, S1, S3);
  if (wg == 1) named_bar_sync(5, 256);
  issue();
  TL(5);
  gather_raw(nb > 1);

  uint32_t eh0 = 0, eh1 = 0, sh0 = 0, sh1 = 0;
  uint32_t k1 = 0, x1 = 0, k2 = 0, x2 = 0;
  uint32_t es1 = sbase + OFF_ES + (tau * 2 + (c & 1)) * 4 + kMaxB * ES_STRIDE, es2 = es1, es3 = es1;
  uint32_t es0 = es1 + (wg - kMaxB) * ES_STRIDE;
  auto reduce = [&]() {
    sts32p(es3, hadd2(k2, x2), fl & 2u);
    k2 = hadd2(k1, x1);
    x2 = shfl_xor<2>(k2);
    const uint32_t t0 = hadd2(__byte_perm(eh0, sh0, 0x5410), __byte_perm(eh0, sh0, 0x7632));
    const uint32_t t1 = hadd2(__byte_perm(eh1, sh1, 0x5410), __byte_perm(eh1, sh1, 0x7632));
    k1 = (fl & 1u) ? t1 : t0;
    x1 = shfl_xor<1>((fl & 1u) ? t0 : t1);
  };
  auto s_chain = [&]() {
    sh0 = hmul2(Af[0], ps[0]);
    sh1 = hmul2(Af[1], ps[0]);
#pragma unroll
    for (int i = 1; i < 16; i++) {
      sh0 = hfma2(Af[2 * i], ps[i], sh0);
      sh1 = hfma2(Af[2 * i + 1], ps[i], sh1);
    }
    asm volatile("" : "+r"(sh0), "+r"(sh1)::"memory");
  };
  auto epilogue = [&]() {
    named_bar_sync(3 + bar_wg, 256);
    wgmma_wait<0>();
    fence_regs(acc);
    fence_regs(S0); fence_regs(S1); fence_regs(S2); fence_regs(S3);
    TLX(12);
    eh0 = hmul2(bias_relu2(acc[0], bs[0]), hs[0]);
    eh1 = hmul2(bias_relu2(acc[1], bs[0]), hs[0]);
#pragma unroll
    for (int i = 1; i < 16; i++) {
      eh0 = hfma2(bias_relu2(acc[2 * i], bs[i]), hs[i], eh0);
      eh1 = hfma2(bias_relu2(acc[2 * i + 1], bs[i]), hs[i], eh1);
    }
    asm volatile("" : "+r"(eh0), "+r"(eh1)::"memory");
  };
  auto bump = [&](uint32_t& r) { asm volatile("add.u32 %0, %0, %1;" : "+r"(r) : "n"(2 * kElem)); };
  int left = nb - 1;
  ra[0] += 2 * kElem; ra[1] += 2 * kElem; ra[5] += 2 * kElem;
  auto tile = [&](auto Tc) {
    constexpr int tt = decltype(Tc)::value;
    TLL(0);
    reduce();
    sched_fence(ck, never);
    uint4 r0, r1;
    const bool cv = left > 0 && (fl & (tt == 1 ? 4u : 8u));
    if (tt == 0) load_vec(S0, ra[3]);
    if (tt == 1) {
      load_vec(S2, ra[4]);
      asm volatile("cp.async.wait_all;" ::: "memory");
    }
    if (tt == 1 || tt == 2) {
      r0 = lds128p<(2 * tt - 2) * kRow>(cv_ptr, cv);
      r1 = lds128p<(2 * tt - 1) * kRow>(cv_ptr, cv);
    }
    if (tt == 2) {
      sched_fence(ck, never);
      load_vec(S1, ra[2]);
    }
    if (tt == 3) {
      if (left == 0 && has_left) {
        named_bar_sync(3, 256);
        const uint32_t q = (uint32_t)(tau * 43) >> 7, sub = tau - 3 * q;
        const uint32_t eb = sbase + OFF_EMB + (q < n_c ? q : 0) * kElem + c * 16;
        const uint32_t w = sub == 0 ? 0x60000e0u : sub == 1 ? 0x320002acu : 0x300001efu;
        ra[0] = eb + (w & 31u) * kRow;
        ra[1] = eb + ((w >> 5) & 31u) * kRow;
        ra[5] = eb + (w >> 25) * kRow;
      }
      load_vec(S0, ra[0]);
    }
    if (tt == 4) {
      load_vec(S3, ra[5]);
      load_vec(S1, ra[1]);
    }
    TLL(4);
    s_chain();
    sched_fence(ck, never);
    if (tt == 0) load_idx(1);
    if (tt == 1 || tt == 2) {
      const uint32_t me_old = me;
      sts128p<(2 * tt - 2) * kRow>(cv_ptr, convert(r0), cv);
      sts128p<(2 * tt - 1) * kRow>(cv_ptr, convert(r1), cv);
      me = cv ? me : me_old;
    }
    if (tt == 2) {
      if (left == min(nb - 1, 1) && !has_left) named_bar_arrive(3, 256);
      named_bar_sync(bar_wg, 128);
    }
    if (tt == 3) gather_raw(left > 1);
    TLL(8);
    TLS();
    epilogue();
    TLL(16);
    if (tt == 0) { products(S1, S3, S0); bump(ra[3]); bump(cv_ptr); }
    if (tt == 1) { products(S1, S0, S2); bump(ra[4]); }
    if (tt == 2) { products(S0, S2, S1); bump(ra[2]); }
    if (tt == 3) { products(S1, S2, S3); }
    if (tt == 4) { products(S0, S1, S3); bump(ra[0]); bump(ra[1]); bump(ra[5]); }
    es3 = es2; es2 = es1; es1 = es0;
    es0 += tt == 4 ? 2 * ES_STRIDE - 4 * 256 : 256;
    TLL(20);
    issue();
  };
#pragma unroll 1
  for (;;) {
    tile(std::integral_constant<int, 0>{});
    tile(std::integral_constant<int, 1>{});
    tile(std::integral_constant<int, 2>{});
    tile(std::integral_constant<int, 3>{});
    if (left == 0 && !has_left) break;
    tile(std::integral_constant<int, 4>{});
    if (left == 0) {
      const uint32_t q = (uint32_t)(tau * 43) >> 7, sub = tau - 3 * q;
      es0 = sbase + OFF_ES + (q < n_c ? q : kMaxB) * ES_STRIDE + (320 + 2 * sub + (c & 1)) * 4;
      break;
    }
    left--;
  }
  TLL(0);
  reduce();
  s_chain();
  sts32p(es2, hadd2(k2, x2), fl & 2u);
  k2 = hadd2(k1, x1);
  x2 = shfl_xor<2>(k2);
  es3 = es1;
  me = redux_max(absmax_bits(me));
  sts32p(sbase + OFF_STAT + 32 + warp * 4, me, lane == 0);
  if (wg == 1) {
    for (int i = (n_c & 1) ? 3 : 0; i > 0; i--) {
      named_bar_sync(5, 256);
      named_bar_arrive(4, 256);
    }
  }
  TLL(8);
  TLS();
  epilogue();
  if (wg == 1) named_bar_arrive(4, 256);
  TLL(16);
  TLS();
  reduce();
  k2 = hadd2(k1, x1);
  x2 = shfl_xor<2>(k2);
  sts32p(es0 + ck, hadd2(k2, x2), fl & 2u);
  TL(6);
  __syncthreads();

  if (warp < n_out) {
    const uint32_t ea = sbase + OFF_ES + warp * ES_STRIDE + lane * 16;
    uint32_t w[12];
    {
      const uint4 v0 = lds128<0>(ea), v1 = lds128<512>(ea), v2 = lds128<1024>(ea - (lane < 18 ? 0 : 512));
      w[0] = v0.x; w[1] = v0.y; w[2] = v0.z; w[3] = v0.w; w[4] = v1.x; w[5] = v1.y; w[6] = v1.z; w[7] = v1.w;
      w[8] = v2.x; w[9] = v2.y; w[10] = v2.z; w[11] = v2.w;
    }
    const uint4 sw0 = lds128<0>(sbase + OFF_STAT), sw1 = lds128<16>(sbase + OFF_STAT);
    const uint4 se0 = lds128<32>(sbase + OFF_STAT), se1 = lds128<48>(sbase + OFF_STAT);
    const uint4 sv0 = lds128<64>(sbase + OFF_STAT), sv1 = lds128<80>(sbase + OFF_STAT);
    const int nvalid = min(max(kP - 256 - 4 * lane, 0), 4);
#pragma unroll
    for (int q = 0; q < 4; q++) w[8 + q] = q < nvalid ? w[8 + q] : w[0];
    uint32_t mx = w[0], ma = w[0];
#pragma unroll
    for (int q = 1; q < 12; q++) {
      mx = hmax2(mx, w[q]);
      ma = habsmax2(ma, w[q]);
    }
    uint32_t mi = mx & 0xffffu;
    mi = (mi & 0x8000u) ? (mi ^ 0xffffu) : (mi | 0x8000u);
    mi = redux_max(mi);
    mi = (mi & 0x8000u) ? (mi ^ 0x8000u) : (mi ^ 0xffffu);
    const uint32_t mae = redux_max(ma & 0x7fffu), mas = redux_max((ma >> 16) & 0x7fffu);
    constexpr float kE = 1.4426950408889634f / 256.f;
    const float mk = h_lo(mi) * kE;
    float l = 0.f, a = 0.f;
#pragma unroll
    for (int q = 0; q < 12; q++) {
      float x;
      asm("ex2.approx.ftz.f32 %0, %1;" : "=f"(x) : "f"(fmaf(h_lo(w[q]), kE, -mk)));
      if (q >= 8 && q - 8 >= nvalid) x = 0.f;
      l += x;
      a = fmaf(x, h_hi(w[q]), a);
    }
#pragma unroll
    for (int o = 16; o > 0; o >>= 1) {
      l += __shfl_xor_sync(0xffffffffu, l, o);
      a += __shfl_xor_sync(0xffffffffu, a, o);
    }
    const float Wm = 128.f * h_lo(max(max(max(sw0.x, sw0.y), max(sw0.z, sw0.w)), max(max(sw1.x, sw1.y), max(sw1.z, sw1.w))));
    const float M = h_lo(max(max(max(se0.x, se0.y), max(se0.z, se0.w)), max(max(se1.x, se1.y), max(se1.z, se1.w))));
    const float Bs = __uint_as_float(sv0.x) + __uint_as_float(sv0.y);
    const float Hs = __uint_as_float(sv0.z) + __uint_as_float(sv0.w);
    const float Ps = __uint_as_float(sv1.x) + __uint_as_float(sv1.y);
    const float M2 = M * M, X = fmaf(M2, Wm, Bs), G = fmaf(2.f, M, 1.f);
    constexpr float u = 1.f / 33554432.f;
    const float de = u * (Hs * (Wm * G + 128.f * M2 + 16.f) + 128.f * X + 256.f);
    const float ds = u * (Ps * G + 128.f * M2 + 256.f);
    const bool ok = M2 <= 60000.f && X <= 60000.f && de <= 1.f && ds <= h_lo(mas) * (1.f / 16384.f) &&
                    mae < 0x7c00u && mas < 0x7c00u;
    if (ok) {
      if (lane == 0) out[b0 + warp] = __float2bfloat16_rn(__fdividef(a, l) * 0.0625f);
    } else {
      general_element(idx + (b0 + warp) * kF, table, ii, jj, W, bias, hvec, pvec, out + b0 + warp,
                      reinterpret_cast<float*>(smem + OFF_EMB + warp * kElem));
    }
  }
  TL(7);
}

}

extern "C" void kernel_launch(void* const* d_in, const int* in_sizes, int n_in, void* d_out, int out_size) {
  const int* idx = (const int*)d_in[0];
  const __nv_bfloat16* table = (const __nv_bfloat16*)d_in[1];
  const int* ii = (const int*)d_in[2];
  const int* jj = (const int*)d_in[3];
  const __nv_bfloat16* W = (const __nv_bfloat16*)d_in[4];
  const __nv_bfloat16* bias = (const __nv_bfloat16*)d_in[5];
  const __nv_bfloat16* hvec = (const __nv_bfloat16*)d_in[6];
  const __nv_bfloat16* pvec = (const __nv_bfloat16*)d_in[7];
  __nv_bfloat16* out = (__nv_bfloat16*)d_out;
  const int B = out_size;

  static int num_sms = 0;
  if (num_sms == 0) {
    int dev = 0;
    cudaGetDevice(&dev);
    cudaDeviceGetAttribute(&num_sms, cudaDevAttrMultiProcessorCount, dev);
    cudaFuncSetAttribute(afm_kernel, cudaFuncAttributeMaxDynamicSharedMemorySize, SMEM_BYTES);
  }
  const Sched sched = {{
    0x2b053f08u, 0x083ab221u, 0x020309afu, 0x11958a4au, 0x22c3a439u, 0x2cd42582u, 0x2b35b402u, 0x29684861u,
    0x2ca8ba64u, 0x26185d03u, 0x3015d9ccu, 0x2f2235d5u, 0x0e4989f4u, 0x08952cd4u, 0x28f89973u, 0x0ac93c16u,
    0x3082c480u, 0x06154b2bu, 0x00871e8au, 0x125ad037u, 0x1b9c1e8au, 0x25848a71u, 0x1c37a5a2u, 0x2e332311u,
    0x1f7b6408u, 0x010c9131u, 0x04d8162fu, 0x2a63da4eu, 0x05462ae3u, 0x0a7bad43u, 0x20c33967u, 0x265cb8ccu
  }};
  int grid = num_sms;
  const int min_grid = (B + kMaxB - 1) / kMaxB;
  if (grid < min_grid) grid = min_grid;
  if (grid > B) grid = B;
  afm_kernel<<<grid, kThreads, SMEM_BYTES>>>(idx, table, ii, jj, W, bias, hvec, pvec, out, B / grid, B % grid,
                                             B * kF - 2, sched);
}
```

```cpp
#include <cuda_runtime.h>
#include <cuda_bf16.h>
#include <cuda_fp16.h>
#include <stdint.h>
#include <type_traits>

#define AFM_R2POS 0
#define AFM_WPOS 0
#define AFM_G1WAIT 1
#define AFM_SPOS 1
#define AFM_MAXFORM 0
#define AFM_HALF 1
#define AFM_WPF 1
#define AFM_WPFN 32
#define AFM_LDELAY 1000
#define AFM_HDELAY 0
#define AFM_RC 216
#define AFM_LDSFIRST 0
#define AFM_LBR 1
#define AFM_S3B 0
#define AFM_TURN2 0
#define AFM_HINT 20000
#define AFM_G1DELAY 200
#define AFM_HSLEEP 300
namespace {

constexpr int kF = 26;
constexpr int kD = 128;
constexpr int kP = 325;
constexpr int kMaxB = 8;
constexpr int kThreads = 384;
constexpr int kRow = 320;
constexpr int kElem = kF * kRow;

constexpr int B_NBLK = 16 * 1024;
constexpr int OFF_B = 0;
constexpr int OFF_EMB = 2 * B_NBLK;
constexpr int OFF_ES = OFF_EMB + kMaxB * kElem;
constexpr int ES_STRIDE = 72 * 16;
constexpr int OFF_VEC = OFF_ES + (kMaxB + 1) * ES_STRIDE;
constexpr int OFF_STAT = OFF_VEC + 768;
constexpr int OFF_BAR = OFF_STAT + 128;
constexpr int SMEM_USED = OFF_EMB + (kMaxB + 2) * kElem;
static_assert(OFF_BAR + 144 <= SMEM_USED, "layout");
constexpr int SMEM_BYTES = SMEM_USED;
static_assert(OFF_ES % 16 == 0 && OFF_VEC % 16 == 0 && OFF_STAT % 16 == 0 && kElem % 128 == 0, "alignment");

struct Sched { uint32_t e[32]; };

__device__ __forceinline__ uint32_t smem_u32(const void* p) { return (uint32_t)__cvta_generic_to_shared(p); }
__device__ __forceinline__ void named_bar_sync(int id, int n) { asm volatile("bar.sync %0, %1;" ::"r"(id), "r"(n) : "memory"); }
__device__ __forceinline__ void named_bar_arrive(int id, int n) { asm volatile("bar.arrive %0, %1;" ::"r"(id), "r"(n) : "memory"); }
template <int A, int B>
__device__ __forceinline__ void bar_sync2(uint32_t sel) {
  asm volatile("{\n.reg .pred p;\nsetp.eq.u32 p, %0, 0;\n@p bar.sync %1, 256;\n@!p bar.sync %2, 256;\n}" ::"r"(sel), "n"(A), "n"(B) : "memory");
}
template <int A, int B>
__device__ __forceinline__ void bar_arrive2(uint32_t sel) {
  asm volatile("{\n.reg .pred p;\nsetp.eq.u32 p, %0, 0;\n@p bar.arrive %1, 256;\n@!p bar.arrive %2, 256;\n}" ::"r"(sel), "n"(A), "n"(B) : "memory");
}
__device__ __forceinline__ void mbar_init(uint32_t bar, uint32_t count) {
  asm volatile("mbarrier.init.shared::cta.b64 [%0], %1;" ::"r"(bar), "r"(count) : "memory");
}
__device__ __forceinline__ void mbar_arrive(uint32_t bar) {
  asm volatile("mbarrier.arrive.shared::cta.b64 _, [%0];" ::"r"(bar) : "memory");
}
__device__ __forceinline__ void mbar_arrive_p(uint32_t bar, bool on) {
  asm volatile("{\n.reg .pred p;\nsetp.ne.u32 p, %1, 0;\n@p mbarrier.arrive.shared::cta.b64 _, [%0];\n}" ::"r"(bar), "r"((uint32_t)on) : "memory");
}
__device__ __forceinline__ void mbar_wait(uint32_t bar, uint32_t parity) {
  uint32_t ok, it = 0;
  do {
    asm volatile("{\n.reg .pred p;\nmbarrier.try_wait.parity.shared::cta.b64 p, [%1], %2, %3;\nselp.u32 %0, 1, 0, p;\n}\n"
                 : "=r"(ok) : "r"(bar), "r"(parity), "r"(AFM_HINT) : "memory");
  } while (!ok && ++it < (1u << 16));
}
__device__ __forceinline__ void wgmma_fence() { asm volatile("wgmma.fence.sync.aligned;" ::: "memory"); }
__device__ __forceinline__ void wgmma_commit() { asm volatile("wgmma.commit_group.sync.aligned;" ::: "memory"); }
template <int N>
__device__ __forceinline__ void wgmma_wait() { asm volatile("wgmma.wait_group.sync.aligned %0;" ::"n"(N) : "memory"); }
__device__ __forceinline__ void fence_proxy_async() { asm volatile("fence.proxy.async.shared::cta;" ::: "memory"); }

__device__ __forceinline__ uint32_t hmul2(uint32_t a, uint32_t b) {
  uint32_t d;
  asm("mul.rn.f16x2 %0, %1, %2;" : "=r"(d) : "r"(a), "r"(b));
  return d;
}
__device__ __forceinline__ uint32_t hadd2(uint32_t a, uint32_t b) {
  uint32_t d;
  asm("add.rn.f16x2 %0, %1, %2;" : "=r"(d) : "r"(a), "r"(b));
  return d;
}
__device__ __forceinline__ uint32_t hfma2(uint32_t a, uint32_t b, uint32_t c) {
  uint32_t d;
  asm("fma.rn.f16x2 %0, %1, %2, %3;" : "=r"(d) : "r"(a), "r"(b), "r"(c));
  return d;
}
__device__ __forceinline__ uint32_t bias_relu2(uint32_t x, uint32_t b) {
  uint32_t d;
  asm("fma.rn.relu.f16x2 %0, %1, %2, %3;" : "=r"(d) : "r"(x), "r"(0x3C003C00u), "r"(b));
  return d;
}
__device__ __forceinline__ uint32_t habsmax2(uint32_t a, uint32_t b) {
  uint32_t d;
  asm("max.NaN.xorsign.abs.f16x2 %0, %1, %2;" : "=r"(d) : "r"(a), "r"(b));
  return d;
}
__device__ __forceinline__ uint32_t babsmax2(uint32_t a, uint32_t b) {
  uint32_t d;
  asm("max.NaN.xorsign.abs.bf16x2 %0, %1, %2;" : "=r"(d) : "r"(a), "r"(b));
  return d;
}
__device__ __forceinline__ uint32_t hmax2(uint32_t a, uint32_t b) {
  uint32_t d;
  asm("max.f16x2 %0, %1, %2;" : "=r"(d) : "r"(a), "r"(b));
  return d;
}
__device__ __forceinline__ uint32_t bf2h(uint32_t x) {
  uint32_t d;
  asm("cvt.rn.f16x2.f32 %0, %1, %2;" : "=r"(d) : "f"(__uint_as_float(x & 0xffff0000u)), "f"(__uint_as_float(x << 16)));
  return d;
}
__device__ __forceinline__ uint32_t bf2h_x16(uint32_t x) {
  uint32_t hi, lo, d;
  asm("fma.rn.bf16x2 %0, %1, %2, %3;" : "=r"(hi) : "r"(x), "r"(0x41800000u), "r"(0u));
  asm("{\n.reg .b16 l, h;\n.reg .b32 t;\nmov.b32 {l, h}, %1;\nmov.b32 t, {l, l};\nfma.rn.bf16x2 %0, t, %2, %3;\n}"
      : "=r"(lo) : "r"(x), "r"(0x41800000u), "r"(0u));
  asm("cvt.rn.f16x2.f32 %0, %1, %2;" : "=r"(d) : "f"(__uint_as_float(hi)), "f"(__uint_as_float(lo)));
  return d;
}
__device__ __forceinline__ uint4 convert(uint4 v) { return make_uint4(bf2h(v.x), bf2h(v.y), bf2h(v.z), bf2h(v.w)); }
__device__ __forceinline__ float h_lo(uint32_t x) { return __half2float(__ushort_as_half((unsigned short)(x & 0xffffu))); }
__device__ __forceinline__ float h_hi(uint32_t x) { return __half2float(__ushort_as_half((unsigned short)(x >> 16))); }
__device__ __forceinline__ uint32_t redux_max(uint32_t v) {
  uint32_t d;
  asm volatile("redux.sync.max.u32 %0, %1, 0xffffffff;" : "=r"(d) : "r"(v));
  return d;
}
__device__ __forceinline__ uint32_t absmax_bits(uint32_t m) { return max(m & 0x7fffu, (m >> 16) & 0x7fffu); }

template <int OFF>
__device__ __forceinline__ uint4 lds128(uint32_t addr) {
  uint4 v;
  asm volatile("ld.shared.v4.u32 {%0,%1,%2,%3}, [%4+%5];" : "=r"(v.x), "=r"(v.y), "=r"(v.z), "=r"(v.w) : "r"(addr), "n"(OFF));
  return v;
}
template <int OFF>
__device__ __forceinline__ void sts128(uint32_t addr, uint4 v) {
  asm volatile("st.shared.v4.u32 [%0+%5], {%1,%2,%3,%4};" ::"r"(addr), "r"(v.x), "r"(v.y), "r"(v.z), "r"(v.w), "n"(OFF) : "memory");
}
__device__ __forceinline__ uint32_t lds32(uint32_t addr) {
  uint32_t v;
  asm volatile("ld.shared.u32 %0, [%1];" : "=r"(v) : "r"(addr));
  return v;
}
__device__ __forceinline__ void sts32(uint32_t addr, uint32_t v) { asm volatile("st.shared.u32 [%0], %1;" ::"r"(addr), "r"(v) : "memory"); }
__device__ __forceinline__ uint32_t ldg32(const void* p) {
  uint32_t v;
  asm volatile("ld.global.u32 %0, [%1];" : "=r"(v) : "l"(p) : "memory");
  return v;
}
__device__ __forceinline__ uint4 ldg128(const void* p) {
  uint4 v;
  asm volatile("ld.global.v4.u32 {%0,%1,%2,%3}, [%4];" : "=r"(v.x), "=r"(v.y), "=r"(v.z), "=r"(v.w) : "l"(p) : "memory");
  return v;
}
__device__ __forceinline__ uint2 ldg64(const void* p) {
  uint2 v;
  asm volatile("ld.global.v2.u32 {%0,%1}, [%2];" : "=r"(v.x), "=r"(v.y) : "l"(p) : "memory");
  return v;
}
__device__ __forceinline__ uint2 ldg64p(const void* p, bool on) {
  uint2 v;
  asm volatile("{\n.reg .pred p;\nsetp.ne.u32 p, %3, 0;\n@p ld.volatile.global.v2.u32 {%0,%1}, [%2];\n}" : "=r"(v.x), "=r"(v.y) : "l"(p), "r"((uint32_t)on) : "memory");
  return v;
}
__device__ __forceinline__ uint4 ldg128p(const void* p, bool on) {
  uint4 v = make_uint4(0u, 0u, 0u, 0u);
  asm volatile("{\n.reg .pred p;\nsetp.ne.u32 p, %5, 0;\n@p ld.global.v4.u32 {%0,%1,%2,%3}, [%4];\n}"
               : "+r"(v.x), "+r"(v.y), "+r"(v.z), "+r"(v.w) : "l"(p), "r"((uint32_t)on) : "memory");
  return v;
}
__device__ __forceinline__ uint4 ldg_row(const void* base, uint32_t row, bool on) {
  uint4 v;
  asm volatile("{\n.reg .pred p;\n.reg .b64 a;\nsetp.ne.u32 p, %6, 0;\nmad.wide.u32 a, %5, 256, %4;\n@p ld.global.v4.u32 {%0,%1,%2,%3}, [a];\n}"
               : "=r"(v.x), "=r"(v.y), "=r"(v.z), "=r"(v.w) : "l"(base), "r"(row), "r"((uint32_t)on) : "memory");
  return v;
}
template <int OFF>
__device__ __forceinline__ uint4 lds128p(uint32_t addr, bool on) {
  uint4 v;
  asm volatile("{\n.reg .pred p;\nsetp.ne.u32 p, %6, 0;\n@p ld.shared.v4.u32 {%0,%1,%2,%3}, [%4+%5];\n}"
               : "=r"(v.x), "=r"(v.y), "=r"(v.z), "=r"(v.w) : "r"(addr), "n"(OFF), "r"((uint32_t)on));
  return v;
}
template <int OFF>
__device__ __forceinline__ void sts128p(uint32_t addr, uint4 v, bool on) {
  asm volatile("{\n.reg .pred p;\nsetp.ne.u32 p, %6, 0;\n@p st.shared.v4.u32 [%0+%5], {%1,%2,%3,%4};\n}"
               ::"r"(addr), "r"(v.x), "r"(v.y), "r"(v.z), "r"(v.w), "n"(OFF), "r"((uint32_t)on) : "memory");
}
__device__ __forceinline__ void sts32p(uint32_t addr, uint32_t v, bool on) {
  asm volatile("{\n.reg .pred p;\nsetp.ne.u32 p, %2, 0;\n@p st.shared.u32 [%0], %1;\n}" ::"r"(addr), "r"(v), "r"((uint32_t)on) : "memory");
}
__device__ __forceinline__ void pin2(uint32_t a, uint32_t b, uint32_t never) {
  asm volatile("{\n.reg .pred p;\nsetp.ne.u32 p, %2, 0;\n@p st.shared.u32 [%0], %1;\n}" ::"r"(a), "r"(b), "r"(never) : "memory");
}
template <int M>
__device__ __forceinline__ uint32_t shfl_xor(uint32_t v) {
  uint32_t d;
  asm volatile("shfl.sync.bfly.b32 %0, %1, %2, 0x1f, 0xffffffff;" : "=r"(d) : "r"(v), "n"(M));
  return d;
}
template <int I, int N, typename F>
__device__ __forceinline__ void static_for(F&& f) {
  if constexpr (I < N) {
    f(std::integral_constant<int, I>{});
    static_for<I + 1, N>(f);
  }
}
template <int N>
__device__ __forceinline__ void fence_regs(uint32_t (&r)[N]) {
#pragma unroll
  for (int i = 0; i < N; i++) asm volatile("" : "+r"(r[i])::"memory");
}
__device__ __forceinline__ void load_vec(uint32_t (&v)[16], uint32_t a) {
  const uint4 v0 = lds128<0>(a), v1 = lds128<64>(a), v2 = lds128<128>(a), v3 = lds128<192>(a);
  v[0] = v0.x; v[1] = v0.y; v[2] = v0.z; v[3] = v0.w; v[4] = v1.x; v[5] = v1.y; v[6] = v1.z; v[7] = v1.w;
  v[8] = v2.x; v[9] = v2.y; v[10] = v2.z; v[11] = v2.w; v[12] = v3.x; v[13] = v3.y; v[14] = v3.z; v[15] = v3.w;
}

__device__ __forceinline__ uint32_t clock32() {
  uint32_t v;
  asm volatile("mov.u32 %0, %%clock;" : "=r"(v)::"memory");
  return v;
}
__device__ __forceinline__ void sched_fence(uint32_t& ck, uint32_t never) {
  asm volatile("{\n.reg .pred p;\nsetp.ne.u32 p, %1, 0;\n@p mov.u32 %0, %%clock;\n}" : "+r"(ck) : "r"(never) : "memory");
}

template <int ACCUM>
__device__ __forceinline__ void wgmma_rs_n128(uint32_t (&d)[32], uint32_t a0, uint32_t a1, uint32_t a2, uint32_t a3, uint64_t descB) {
  if (ACCUM == 1) {
    asm volatile(
        "wgmma.mma_async.sync.aligned.m64n128k16.f16.f16.f16 "
        "{%0, %1, %2, %3, %4, %5, %6, %7, %8, %9, %10, %11, %12, %13, %14, %15, %16, %17, %18, %19, %20, %21, %22, %23, %24, %25, %26, %27, %28, %29, %30, %31}, "
        "{%32, %33, %34, %35}, %36, 1, 1, 1, 1;\n"
        : "+r"(d[0]), "+r"(d[1]), "+r"(d[2]), "+r"(d[3]), "+r"(d[4]), "+r"(d[5]), "+r"(d[6]), "+r"(d[7]), "+r"(d[8]), "+r"(d[9]), "+r"(d[10]), "+r"(d[11]), "+r"(d[12]), "+r"(d[13]), "+r"(d[14]), "+r"(d[15]), "+r"(d[16]), "+r"(d[17]), "+r"(d[18]), "+r"(d[19]), "+r"(d[20]), "+r"(d[21]), "+r"(d[22]), "+r"(d[23]), "+r"(d[24]), "+r"(d[25]), "+r"(d[26]), "+r"(d[27]), "+r"(d[28]), "+r"(d[29]), "+r"(d[30]), "+r"(d[31])
        : "r"(a0), "r"(a1), "r"(a2), "r"(a3), "l"(descB));
  }
  if (ACCUM == 0) {
    asm volatile(
        "wgmma.mma_async.sync.aligned.m64n128k16.f16.f16.f16 "
        "{%0, %1, %2, %3, %4, %5, %6, %7, %8, %9, %10, %11, %12, %13, %14, %15, %16, %17, %18, %19, %20, %21, %22, %23, %24, %25, %26, %27, %28, %29, %30, %31}, "
        "{%32, %33, %34, %35}, %36, 0, 1, 1, 1;\n"
        : "=r"(d[0]), "=r"(d[1]), "=r"(d[2]), "=r"(d[3]), "=r"(d[4]), "=r"(d[5]), "=r"(d[6]), "=r"(d[7]), "=r"(d[8]), "=r"(d[9]), "=r"(d[10]), "=r"(d[11]), "=r"(d[12]), "=r"(d[13]), "=r"(d[14]), "=r"(d[15]), "=r"(d[16]), "=r"(d[17]), "=r"(d[18]), "=r"(d[19]), "=r"(d[20]), "=r"(d[21]), "=r"(d[22]), "=r"(d[23]), "=r"(d[24]), "=r"(d[25]), "=r"(d[26]), "=r"(d[27]), "=r"(d[28]), "=r"(d[29]), "=r"(d[30]), "=r"(d[31])
        : "r"(a0), "r"(a1), "r"(a2), "r"(a3), "l"(descB));
  }
}
__device__ __forceinline__ void wgmma_rs_n128_p(uint32_t (&d)[32], uint32_t a0, uint32_t a1, uint32_t a2, uint32_t a3, uint64_t descB, uint32_t accum) {
  asm volatile(
      "{\n.reg .pred p;\nsetp.ne.u32 p, %37, 0;\n"
      "wgmma.mma_async.sync.aligned.m64n128k16.f16.f16.f16 "
      "{%0, %1, %2, %3, %4, %5, %6, %7, %8, %9, %10, %11, %12, %13, %14, %15, %16, %17, %18, %19, %20, %21, %22, %23, %24, %25, %26, %27, %28, %29, %30, %31}, "
      "{%32, %33, %34, %35}, %36, p, 1, 1, 1;\n}\n"
      : "+r"(d[0]), "+r"(d[1]), "+r"(d[2]), "+r"(d[3]), "+r"(d[4]), "+r"(d[5]), "+r"(d[6]), "+r"(d[7]), "+r"(d[8]), "+r"(d[9]), "+r"(d[10]), "+r"(d[11]), "+r"(d[12]), "+r"(d[13]), "+r"(d[14]), "+r"(d[15]), "+r"(d[16]), "+r"(d[17]), "+r"(d[18]), "+r"(d[19]), "+r"(d[20]), "+r"(d[21]), "+r"(d[22]), "+r"(d[23]), "+r"(d[24]), "+r"(d[25]), "+r"(d[26]), "+r"(d[27]), "+r"(d[28]), "+r"(d[29]), "+r"(d[30]), "+r"(d[31])
      : "r"(a0), "r"(a1), "r"(a2), "r"(a3), "l"(descB), "r"(accum));
}

#define TL(slot) sched_fence(ck, never)
#define TLL(off) sched_fence(ck, never)
#define TLX(off)
#define TLS()

#define TH(slot)
__device__ __forceinline__ float rbf(float x) { return __bfloat162float(__float2bfloat16_rn(x)); }
__device__ __forceinline__ float warp_sum(float v) {
#pragma unroll
  for (int o = 16; o > 0; o >>= 1) v += __shfl_xor_sync(0xffffffffu, v, o);
  return v;
}

__device__ __noinline__ void general_element(const int* __restrict__ idx, const __nv_bfloat16* __restrict__ table,
                                             const int* __restrict__ ii, const int* __restrict__ jj,
                                             const __nv_bfloat16* __restrict__ W, const __nv_bfloat16* __restrict__ bias,
                                             const __nv_bfloat16* __restrict__ hvec, const __nv_bfloat16* __restrict__ pvec,
                                             __nv_bfloat16* __restrict__ out, float* ev) {
  const int lane = threadIdx.x & 31;
  auto pair4 = [&](int p, float (&pr)[4]) {
    const __nv_bfloat16* a = table + (size_t)idx[ii[p]] * kD + 4 * lane;
    const __nv_bfloat16* b = table + (size_t)idx[jj[p]] * kD + 4 * lane;
#pragma unroll
    for (int q = 0; q < 4; q++) pr[q] = rbf(__bfloat162float(a[q]) * __bfloat162float(b[q]));
  };
  float m = -INFINITY;
  bool has_nan = false;
  for (int p = 0; p < kP; p++) {
    float pr[4], x[4] = {0.f, 0.f, 0.f, 0.f};
    pair4(p, pr);
    for (int l = 0; l < 32; l++) {
#pragma unroll
      for (int q = 0; q < 4; q++) {
        const float v = __shfl_sync(0xffffffffu, pr[q], l);
        const uint2 w = *reinterpret_cast<const uint2*>(W + (4 * l + q) * kD + 4 * lane);
        x[0] = fmaf(v, __uint_as_float(w.x << 16), x[0]);
        x[1] = fmaf(v, __uint_as_float(w.x & 0xffff0000u), x[1]);
        x[2] = fmaf(v, __uint_as_float(w.y << 16), x[2]);
        x[3] = fmaf(v, __uint_as_float(w.y & 0xffff0000u), x[3]);
      }
    }
    float e = 0.f;
#pragma unroll
    for (int q = 0; q < 4; q++) {
      const float y = rbf(rbf(x[q]) + __bfloat162float(bias[4 * lane + q]));
      e = fmaf(rbf(0.5f * rbf(y + fabsf(y))), __bfloat162float(hvec[4 * lane + q]), e);
    }
    e = rbf(warp_sum(e));
    has_nan |= (e != e);
    m = fmaxf(m, e);
    if (lane == 0) ev[p] = e;
  }
  __syncwarp();
  float l = 0.f;
  for (int p = lane; p < kP; p += 32) l += expf(ev[p] - m);
  l = warp_sum(l);
  float pooled[4] = {0.f, 0.f, 0.f, 0.f};
  for (int p = 0; p < kP; p++) {
    float pr[4];
    pair4(p, pr);
    const float al = rbf(expf(ev[p] - m) / l);
#pragma unroll
    for (int q = 0; q < 4; q++) pooled[q] = fmaf(al, pr[q], pooled[q]);
  }
  float o = 0.f;
#pragma unroll
  for (int q = 0; q < 4; q++) o = fmaf(rbf(pooled[q]), __bfloat162float(pvec[4 * lane + q]), o);
  o = warp_sum(o);
  if (has_nan) o = __int_as_float(0x7fffffff);
  if (lane == 0) *out = __float2bfloat16_rn(o);
}

__device__ __forceinline__ void helper_rest(const int* __restrict__ idx, const __nv_bfloat16* __restrict__ table,
                                            const int* __restrict__ ii, const int* __restrict__ jj,
                                            int base_cnt, int extra, int last_row) {
  constexpr uint32_t sbase = 0x400u;
  uint32_t tid, cta;
  asm volatile("mov.u32 %0, %%tid.x;\nmov.u32 %1, %%ctaid.x;" : "=r"(tid), "=r"(cta));
  const int t = tid & 127, lane = tid & 31, wq = (tid >> 5) & 3;
  const int n_c = max(base_cnt + ((int)cta < extra ? 1 : 0), 2);
  const int grp = 7 - (t >> 4);
  const bool v01 = grp < 7, v23 = grp < 6;
  int irow = (cta * base_cnt + min((int)cta, extra) + 2) * kF + 4 * grp;
  uint2 gi01 = ldg64(idx + min(irow, last_row));
  uint2 gi23 = ldg64(idx + min(irow + 2, last_row));
  const __nv_bfloat16* gsrc = table + (t & 15) * 8;
  uint32_t cv_ptr = sbase + OFF_EMB + 2 * kElem + 4 * grp * kRow + (t & 15) * 16;
  uint32_t me = 0;
  auto track = [&](const uint4& a, const uint4& b, bool on) {
    const uint32_t m = babsmax2(babsmax2(babsmax2(a.x, a.y), babsmax2(a.z, a.w)), babsmax2(babsmax2(b.x, b.y), babsmax2(b.z, b.w)));
    me = babsmax2(me, on ? m : 0u);
  };
  named_bar_sync(6, 160);
  if (AFM_HDELAY) __nanosleep(AFM_HDELAY);
#pragma unroll 1
  for (int e = 2; e < n_c; e++) {
    const uint4 g0 = ldg_row(gsrc, gi01.x, v01), g1 = ldg_row(gsrc, gi01.y, v01);
    const uint4 g2 = ldg_row(gsrc, gi23.x, v23), g3 = ldg_row(gsrc, gi23.y, v23);
    irow += kF;
    gi01 = ldg64(idx + min(irow, last_row));
    gi23 = ldg64(idx + min(irow + 2, last_row));
    sts128p<0>(cv_ptr, convert(g0), v01);
    sts128p<kRow>(cv_ptr, convert(g1), v01);
    sts128p<2 * kRow>(cv_ptr, convert(g2), v23);
    sts128p<3 * kRow>(cv_ptr, convert(g3), v23);
    track(g0, g1, v01);
    track(g2, g3, v23);
    cv_ptr += kElem;
    __syncwarp();
    if (lane == 0) mbar_arrive(sbase + OFF_BAR + 8 * e);
    if (AFM_HSLEEP && e >= 3) __nanosleep(AFM_HSLEEP);
  }
  TH(7);
  bool ok_cta;
  float ds;
  {
    mbar_wait(sbase + OFF_BAR + 64, 0);
    mbar_wait(sbase + OFF_BAR + 72, 0);
    uint32_t mh = 0;
#pragma unroll 1
    for (int r = t >> 4; r < 2 * kF; r += 8) {
      const uint4 v = lds128<0>(sbase + OFF_EMB + r * kRow + (t & 15) * 16);
      mh = habsmax2(habsmax2(mh, v.x), habsmax2(v.y, habsmax2(v.z, v.w)));
    }
    me = max(absmax_bits(me), (__float_as_uint(h_lo(absmax_bits(mh))) + 0xffffu) >> 16);
    const uint32_t s0 = lds32(sbase + OFF_VEC + t * 4), s1 = lds32(sbase + OFF_VEC + 512 + (t & 63) * 4);
    float v0 = fabsf(h_lo(s0)) + fabsf(h_hi(s0)), v1 = fabsf(h_lo(s1)) + fabsf(h_hi(s1));
#pragma unroll
    for (int r = 0; r < 3; r++) {
      const uint32_t p = min(t + 128 * r, kP - 1), i = ldg32(ii + p), j = ldg32(jj + p);
      if (!(i < j && j < kF && ((i * (2 * kF - 1 - i)) >> 1) + j - i - 1 == p)) v0 = __int_as_float(0x7fffffff);
    }
    v0 = warp_sum(v0);
    v1 = warp_sum(v1);
    me = redux_max(me);
    if (lane == 0) {
      sts32(sbase + OFF_STAT + 16 + wq * 4, me);
      sts32(sbase + OFF_STAT + 64 + wq * 4, __float_as_uint(v0));
      sts32(sbase + OFF_STAT + 80 + wq * 4, __float_as_uint(v1));
    }
    named_bar_sync(6, 128);
    const uint32_t st = lds32(sbase + OFF_STAT + lane * 4);
    const float Wm = 2048.f * __uint_as_float(redux_max(lane < 4 ? st : 0u) << 16);
    const float M = __uint_as_float(redux_max(lane >= 4 && lane < 8 ? st : 0u) << 16);
    const float sp = __uint_as_float(st) + __shfl_xor_sync(0xffffffffu, __uint_as_float(st), 1);
    const float Bs = __shfl_sync(0xffffffffu, sp, 16);
    const float Hs = __shfl_sync(0xffffffffu, sp, 18);
    const float Ps = __shfl_sync(0xffffffffu, sp, 20);
    const float M2 = M * M, X = fmaf(M2, Wm, Bs), G = fmaf(2.f, M, 1.f);
    constexpr float u = 1.f / 33554432.f;
    const float de = u * (Hs * (Wm * G + 128.f * M2 + 16.f) + 128.f * X + 256.f);
    ds = u * (Ps * G + 128.f * M2 + 256.f);
    ok_cta = M2 <= 60000.f && Wm <= 128.f * 60000.f && X <= 60000.f && de <= 1.f;
  }
  TH(8);
#pragma unroll 1
  for (int e = wq; e < n_c; e += 4) {
    mbar_wait(sbase + OFF_BAR + 64 + 8 * e, 0);
    const uint32_t ea = sbase + OFF_ES + e * ES_STRIDE + lane * 16;
    const uint4 p0 = lds128<0>(ea), p1 = lds128<512>(ea);
    float l = __uint_as_float(p0.x) + __uint_as_float(p1.x), a = __uint_as_float(p0.y) + __uint_as_float(p1.y);
    const uint32_t mx = habsmax2(p0.z, p1.z);
    const uint32_t mae = redux_max(mx & 0x7fffu), mas = redux_max(mx >> 16 & 0x7fffu);
    l = warp_sum(l);
    a = warp_sum(a);
    const bool ok = ok_cta && mae <= 0x7000u && mas < 0x7c00u && ds <= h_lo(mas) * (1.f / 16384.f);
    sts128p<1024>(ea, make_uint4(__float_as_uint(l), __float_as_uint(a), ok ? 1u : 0u, 0u), lane == 0);
  }
  TH(9);
  named_bar_arrive(9, 256);
}

__global__ void __launch_bounds__(kThreads, 1)
afm_kernel(const int* __restrict__ idx, const __nv_bfloat16* __restrict__ table, const __nv_bfloat16* __restrict__ W,
           int base_cnt, int extra, int last_row,
           const int* __restrict__ ii, const int* __restrict__ jj, const __nv_bfloat16* __restrict__ bias,
           const __nv_bfloat16* __restrict__ hvec, const __nv_bfloat16* __restrict__ pvec,
           __nv_bfloat16* __restrict__ out, const __grid_constant__ Sched sched) {
  extern __shared__ __align__(1024) uint8_t smem[];
  constexpr uint32_t sbase = 0x400u;

  const int tid = threadIdx.x;
  const int t = tid & 127;
  const int lane = tid & 31;
  const int warp = tid >> 5;
  uint32_t ck = 0;
  const uint32_t never = tid >> 10;
  const int cta = blockIdx.x;
  const int b0 = cta * base_cnt + min(cta, extra);
  const int grp = 7 - (t >> 4);
  const bool v01 = grp < 7, v23 = grp < 6;
  int irow = (b0 + (tid >> 7)) * kF + 4 * grp;
  uint2 gi01 = ldg64p(idx + min(irow, last_row), tid < 256);
  uint2 gi23 = ldg64p(idx + min(irow + 2, last_row), tid < 256);
  asm volatile("{\n.reg .pred p;\nsetp.ge.u32 p, %1, %2;\n@p prefetch.global.L2 [%0];\n}" ::"l"(W + ((cta * AFM_WPFN + tid) & 255) * 64), "r"(tid), "n"(384 - AFM_WPFN) : "memory");
  sched_fence(ck, never);
  TL(1);
  const int wq = warp & 3;
  const int wg = __shfl_sync(0xffffffffu, tid >> 7, 0);
  const int n_out = base_cnt + (cta < extra ? 1 : 0);
  const int n_c = max(n_out, 2);
  const __nv_bfloat16* gsrc = table + (t & 15) * 8;
  asm volatile("" : "+l"(gsrc));
  uint32_t cv_ptr = sbase + OFF_EMB + wg * kElem + 4 * grp * kRow + (t & 15) * 16;

  if (wg < 2) {
    const int c = lane & 3;
    const int tau = t >> 2;
    asm volatile("{\n.reg .pred p;\nsetp.lt.u32 p, %2, 192;\n@p cp.async.ca.shared.global [%0], [%1], 4;\ncp.async.commit_group;\n}"
                 ::"r"(sbase + OFF_ES + tid * 4), "l"((tid < 64 ? bias : tid < 128 ? hvec : pvec) + 2 * (tid & 63)), "r"(tid) : "memory");
    if (warp == 7) {
      if (lane == 0) {
#pragma unroll
        for (int i = 0; i < 17; i++) mbar_init(sbase + OFF_BAR + 8 * i, i < 2 ? 1 : 4);
        mbar_arrive(sbase + OFF_BAR);
        mbar_arrive(sbase + OFF_BAR + 8);
      }
      if (smem_u32(smem) != sbase) __trap();
      __syncwarp();
      named_bar_arrive(6, 160);
    }
    const int nb = (n_c - wg + 1) >> 1;
    const bool has_left = wg == 0;
    const uint32_t fl = shfl_xor<0>((c & 1) | (c < 2 ? 2u : 0u) | (lane == 0 ? 4u : 0u));
    const uint32_t sc = sched.e[tau];
    uint4 g0[4];
    auto gather_first = [&]() {
      g0[0] = ldg_row(gsrc, gi01.x, v01);
      g0[1] = ldg_row(gsrc, gi01.y, v01);
      g0[2] = ldg_row(gsrc, gi23.x, v23);
      g0[3] = ldg_row(gsrc, gi23.y, v23);
    };
    TL(2);
    auto small_vectors = [&]() {
      asm volatile("cp.async.wait_group 0;" ::: "memory");
      sts32p(sbase + OFF_VEC + (tid < 128 ? ((tid & 112u) | ((tid & 3u) << 2) | ((tid >> 2) & 3u)) : tid) * 4,
             bf2h_x16(lds32(sbase + OFF_ES + tid * 4)) ^ (AFM_MAXFORM && tid < 64 ? 0x80008000u : 0u), tid < 192);
    };
    const uint32_t gdelay = (wg == 1 ? AFM_G1DELAY : 0) + (extra > 0 && cta >= extra ? AFM_LDELAY : 0);
    if (gdelay) {
      uint32_t t0;
      asm volatile("{\n.reg .pred p;\nsetp.lt.s32 p, %1, 0;\n@p trap;\nmov.u32 %0, %%clock;\n}" : "=r"(t0) : "r"(gi01.x | gi23.x) : "memory");
      while (clock32() - t0 < gdelay) {
      }
    }
    sched_fence(ck, never);
    gather_first();
    TL(3);
    small_vectors();
    named_bar_sync(1, 256);
    TL(5);
    uint32_t bs[16], hs[16], ps[16];
    load_vec(ps, sbase + OFF_VEC + 512 + c * 16);
    load_vec(bs, sbase + OFF_VEC + c * 16);
    load_vec(hs, sbase + OFF_VEC + 256 + c * 16);
    TL(4);
    if (wg == 1) named_bar_sync(7, 256);
    asm volatile("setmaxnreg.inc.sync.aligned.u32 %0;" ::"n"(AFM_RC));
    if (wg == 0) named_bar_arrive(7, 256);
    uint32_t ra[6];
#pragma unroll
    for (int r = 0; r < 6; r++) ra[r] = sbase + OFF_EMB + wg * kElem + c * 16 + ((sc >> (5 * r)) & 31u) * kRow;
    asm volatile("" : "+r"(ra[0]), "+r"(ra[1]), "+r"(ra[2]), "+r"(ra[3]), "+r"(ra[4]), "+r"(ra[5]));
    TL(6);
    sts128p<0>(cv_ptr, convert(g0[0]), v01);
    sts128p<kRow>(cv_ptr, convert(g0[1]), v01);
    sched_fence(ck, never);
    sts128p<2 * kRow>(cv_ptr, convert(g0[2]), v23);
    sts128p<3 * kRow>(cv_ptr, convert(g0[3]), v23);
    TL(9);
    named_bar_sync(wg == 0 ? 3 : 2, wg == 0 ? 256 : 128);
    TL(10);

    uint32_t Af[32], acc[32], S0[16], S1[16], S2[16], S3[16];
    load_vec(S3, ra[5]);
    load_vec(S0, ra[0]);
    load_vec(S1, ra[1]);
    constexpr uint64_t dB = (uint64_t)(((sbase + OFF_B) & 0x3FFFFu) >> 4) | ((uint64_t)(B_NBLK >> 4) << 16) |
                            ((uint64_t)(1024 >> 4) << 32) | ((uint64_t)1 << 62);
    auto products = [&](const uint32_t (&X)[16], const uint32_t (&Y)[16], const uint32_t (&Z)[16]) {
#pragma unroll
      for (int i = 0; i < 16; i++) {
        Af[2 * i] = hmul2(X[i], Z[i]);
        Af[2 * i + 1] = hmul2(Y[i], Z[i]);
      }
    };
    auto issue = [&]() {
      fence_regs(Af);
      wgmma_fence();
#pragma unroll
      for (int s = 0; s < 8; s++) {
        const uint64_t d = dB + (uint64_t)(s * (2048 >> 4));
        if (s == 0) wgmma_rs_n128<0>(acc, Af[0], Af[1], Af[2], Af[3], d);
        else wgmma_rs_n128<1>(acc, Af[4 * s], Af[4 * s + 1], Af[4 * s + 2], Af[4 * s + 3], d);
      }
      wgmma_commit();
      bar_arrive2<5, 4>(wg);
    };
#pragma unroll
    for (int i = 0; i < 16; i++) S2[i] = 0;
    products(S0, S1, S3);
    if (wg == 1) named_bar_sync(5, 256);
    TL(11);
    issue();
    TL(12);

    uint32_t eh0 = 0, eh1 = 0, sh0 = 0, sh1 = 0;
    uint32_t k1 = 0, x1 = 0, k2 = 0, x2 = 0, ma = 0;
    float lsum = 0.f, asum = 0.f;
    uint32_t pt_ptr = sbase + OFF_ES + (tau * 2 + (c & 1)) * 16 + kMaxB * ES_STRIDE;
    uint32_t pt_next = pt_ptr + (wg - kMaxB) * ES_STRIDE;
    uint32_t dn_bar = sbase + OFF_BAR + 128, el = wg;
    float w3, s3;
    auto stage3a = [&]() {
      const uint32_t es = hadd2(k2, x2);
      asm volatile("ex2.approx.ftz.f32 %0, %1;" : "=f"(w3) : "f"(h_lo(es) * (1.4426950408889634f / 256.f)));
      ma = habsmax2(ma, es);
      s3 = h_hi(es);
    };
    auto stage3b = [&]() {
      lsum += w3;
      asum = fmaf(w3, s3, asum);
    };
    auto stage3 = [&]() {
      stage3a();
      stage3b();
    };
    auto stage2 = [&]() {
      k2 = hadd2(k1, x1);
      x2 = shfl_xor<2>(k2);
    };
    auto stage1 = [&]() {
      const uint32_t t0 = hadd2(__byte_perm(eh0, sh0, 0x5410), __byte_perm(eh0, sh0, 0x7632));
      const uint32_t t1 = hadd2(__byte_perm(eh1, sh1, 0x5410), __byte_perm(eh1, sh1, 0x7632));
      k1 = (fl & 1u) ? t1 : t0;
      x1 = shfl_xor<1>((fl & 1u) ? t0 : t1);
    };
    auto dump = [&]() {
      sts128p<0>(pt_ptr, make_uint4(__float_as_uint(lsum), __float_as_uint(asum), ma, 0u), fl & 2u);
      lsum = 0.f; asum = 0.f; ma = 0;
      __syncwarp();
      mbar_arrive_p(dn_bar, fl & 4u);
    };
    auto s_chain = [&]() {
      sh0 = hmul2(Af[0], ps[0]);
      sh1 = hmul2(Af[1], ps[0]);
#pragma unroll
      for (int i = 1; i < 16; i++) {
        sh0 = hfma2(Af[2 * i], ps[i], sh0);
        sh1 = hfma2(Af[2 * i + 1], ps[i], sh1);
      }
      asm volatile("" : "+r"(sh0), "+r"(sh1)::"memory");
    };
    auto epilogue = [&]() {
      wgmma_wait<0>();
      fence_regs(acc);
      fence_regs(S0); fence_regs(S1); fence_regs(S2); fence_regs(S3);
      TLX(12);
      eh0 = hmul2(bias_relu2(acc[0], bs[0]), hs[0]);
      eh1 = hmul2(bias_relu2(acc[1], bs[0]), hs[0]);
#pragma unroll
      for (int i = 1; i < 16; i++) {
        eh0 = hfma2(bias_relu2(acc[2 * i], bs[i]), hs[i], eh0);
        eh1 = hfma2(bias_relu2(acc[2 * i + 1], bs[i]), hs[i], eh1);
      }
      asm volatile("" : "+r"(eh0), "+r"(eh1)::"memory");
    };
    auto bump = [&](uint32_t& r) { asm volatile("add.u32 %0, %0, %1;" : "+r"(r) : "n"(2 * kElem)); };
    int left = nb - 1;
    ra[0] += 2 * kElem; ra[1] += 2 * kElem; ra[5] += 2 * kElem;
    uint4 r0, r1;
    auto tile = [&](auto Tc) {
      constexpr int tt = decltype(Tc)::value;
      TLL(0);
      stage3a();
      stage2();
      stage1();
      stage3b();
      asm volatile("" : "+f"(lsum), "+f"(asum));
      asm volatile("" : "+f"(s3), "+r"(ma));
      sched_fence(ck, never);
      if (tt == 0) load_vec(S0, ra[3]);
      if (tt == 1) load_vec(S2, ra[4]);
      if (tt == 2) load_vec(S1, ra[2]);
      if (tt == 3) {
        if (left == 0 && has_left) {
          asm volatile("bar.warp.sync 0xffffffff;" ::: "memory");
          const uint32_t q = tau >> 2, sub = tau & 3;
          const uint32_t eb = sbase + OFF_EMB + (q < n_c ? q : 0) * kElem + c * 16;
          const uint32_t w = sub == 0 ? 0x60000e0u : sub == 1 ? 0x320002acu : 0x300001efu;
          ra[0] = eb + (w & 31u) * kRow;
          ra[1] = eb + ((w >> 5) & 31u) * kRow;
          ra[5] = eb + (w >> 25) * kRow;
        }
        load_vec(S0, ra[0]);
        r0 = lds128<0>(ra[1]);
        r1 = lds128<64>(ra[1]);
      }
      if (tt == 4) {
        load_vec(S3, ra[5]);
        const uint4 v2 = lds128<128>(ra[1]), v3 = lds128<192>(ra[1]);
        S1[8] = v2.x; S1[9] = v2.y; S1[10] = v2.z; S1[11] = v2.w; S1[12] = v3.x; S1[13] = v3.y; S1[14] = v3.z; S1[15] = v3.w;
        S1[0] = r0.x; S1[1] = r0.y; S1[2] = r0.z; S1[3] = r0.w; S1[4] = r1.x; S1[5] = r1.y; S1[6] = r1.z; S1[7] = r1.w;
      }
      TLL(4);
      s_chain();
      if (tt == 2) sched_fence(ck, never);
      if (tt == 2) {
        dump();
        mbar_wait(sbase + OFF_BAR + 8 * min(el + 2, n_c - 1), 0);
      }
      TLL(8);
      TLS();
      epilogue();
      TLL(16);
      if (tt == 0) { products(S1, S3, S0); bump(ra[3]); }
      if (tt == 1) { products(S1, S0, S2); bump(ra[4]); }
      if (tt == 2) { products(S0, S2, S1); bump(ra[2]); }
      if (tt == 3) {
        products(S1, S2, S3);
        pt_ptr = pt_next;
        pt_next += 2 * ES_STRIDE;
        dn_bar = sbase + OFF_BAR + 64 + 8 * el;
        el += 2;
      }
      if (tt == 4) { products(S0, S1, S3); bump(ra[0]); bump(ra[1]); bump(ra[5]); }
      TLL(20);
      bar_sync2<4, 5>(wg);
      issue();
    };
#pragma unroll 1
    for (;;) {
      tile(std::integral_constant<int, 0>{});
      tile(std::integral_constant<int, 1>{});
      tile(std::integral_constant<int, 2>{});
      tile(std::integral_constant<int, 3>{});
      if (left == 0 && !has_left) break;
      tile(std::integral_constant<int, 4>{});
      if (left == 0) break;
      left--;
    }
    TLL(0);
    stage3();
    stage2();
    stage1();
    s_chain();
    stage3();
    stage2();
    stage3();
    if (has_left) dump();
    __nv_bfloat16* const op = out + b0 + (t >> 4);
    const bool valid = 2 * (tau & 3) + (c & 1) < 5, writer = (t & 15) == 0 && (t >> 4) < n_out;
    TLL(8);
    TLS();
    epilogue();
    TLL(16);
    TLS();
    stage1();
    if (!has_left) {
      stage2();
      stage3();
      pt_ptr += ck;
      dump();
      TL(13);
      for (int i = (n_c & 1) ? 5 : 0; i > 0; i--) {
        named_bar_sync(5, 256);
        named_bar_arrive(4, 256);
      }
      named_bar_sync(5, 256);
    } else {
      TL(13);
      named_bar_sync(9, 256);
      TL(14);
      const uint4 tot = lds128<1024>(sbase + OFF_ES + (t >> 4) * ES_STRIDE + ck);
      stage2();
      stage3();
      float l = valid ? lsum : 0.f, a = valid ? asum : 0.f;
      const uint32_t bad = __ballot_sync(0xffffffffu, (ma & 0x7fffu) > 0x7000u || ((ma >> 16) & 0x7fffu) >= 0x7c00u || tot.z == 0u);
      l += __shfl_xor_sync(0xffffffffu, l, 1);
      a += __shfl_xor_sync(0xffffffffu, a, 1);
      l += __shfl_xor_sync(0xffffffffu, l, 4);
      a += __shfl_xor_sync(0xffffffffu, a, 4);
      l += __shfl_xor_sync(0xffffffffu, l, 8);
      a += __shfl_xor_sync(0xffffffffu, a, 8);
      float r;
      asm("rcp.approx.ftz.f32 %0, %1;" : "=f"(r) : "f"(l + __uint_as_float(tot.x)));
      if (writer) *op = __float2bfloat16_rn((a + __uint_as_float(tot.y)) * r * 0.0625f);
      if (bad) {
        for (int h = 0; h < 2; h++) {
          const int q = 2 * warp + h;
          if (((bad >> (16 * h)) & 0xffffu) && q < n_out) {
            __syncwarp();
            general_element(idx + (b0 + q) * kF, table, ii, jj, W, bias, hvec, pvec, out + b0 + q,
                            reinterpret_cast<float*>(smem + OFF_EMB + warp * kElem));
          }
        }
      }
    }
  } else {
    {
      asm volatile("setmaxnreg.dec.sync.aligned.u32 104;");
      uint4 wr[16];
#pragma unroll
      for (int r = 0; r < 16; r++) wr[r] = ldg128(W + (32 * wq + 2 * r) * kD + 8 * lane);
      const uint32_t wa = sbase + OFF_B + ((lane >> 3) & 1) * B_NBLK + wq * 4096 + (lane >> 4) * 128;
      const uint32_t lx = (lane & 7) ^ (lane >> 4);
      uint32_t wad[4], mw = 0;
#pragma unroll
      for (int x = 0; x < 4; x++) wad[x] = wa + ((lx ^ (2 * x)) << 4);
      TL(2);
      TL(3);
      static_for<0, 16>([&](auto Rc) {
        constexpr int r = decltype(Rc)::value;
        uint4 v;
        v.x = bf2h_x16(wr[r].x); v.y = bf2h_x16(wr[r].y); v.z = bf2h_x16(wr[r].z); v.w = bf2h_x16(wr[r].w);
        sts128<(r & 3) * 1024 + (r >> 2) * 256>(wad[r >> 2], v);
        mw = babsmax2(babsmax2(mw, wr[r].x), babsmax2(wr[r].y, babsmax2(wr[r].z, wr[r].w)));
        if (r == 3) TL(4);
        if (r == 7 || r == 11) sched_fence(ck, never);
      });
      TL(5);
      fence_proxy_async();
      named_bar_arrive(3, 256);
      TL(6);
      sts32p(sbase + OFF_STAT + wq * 4 + ck, redux_max(absmax_bits(mw)), lane == 0);
    }
    asm volatile("setmaxnreg.dec.sync.aligned.u32 %0;" ::"n"(504 - 2 * AFM_RC));
    helper_rest(idx, table, ii, jj, base_cnt, extra, last_row);
  }
}

}

extern "C" void kernel_launch(void* const* d_in, const int* in_sizes, int n_in, void* d_out, int out_size) {
  const int* idx = (const int*)d_in[0];
  const __nv_bfloat16* table = (const __nv_bfloat16*)d_in[1];
  const int* ii = (const int*)d_in[2];
  const int* jj = (const int*)d_in[3];
  const __nv_bfloat16* W = (const __nv_bfloat16*)d_in[4];
  const __nv_bfloat16* bias = (const __nv_bfloat16*)d_in[5];
  const __nv_bfloat16* hvec = (const __nv_bfloat16*)d_in[6];
  const __nv_bfloat16* pvec = (const __nv_bfloat16*)d_in[7];
  __nv_bfloat16* out = (__nv_bfloat16*)d_out;
  const int B = out_size;

  static int num_sms = 0;
  if (num_sms == 0) {
    int dev = 0;
    cudaGetDevice(&dev);
    cudaDeviceGetAttribute(&num_sms, cudaDevAttrMultiProcessorCount, dev);
    cudaFuncSetAttribute(afm_kernel, cudaFuncAttributeMaxDynamicSharedMemorySize, SMEM_BYTES);
  }
  const Sched sched = {{
    0x2b053f08u, 0x083ab221u, 0x020309afu, 0x11958a4au, 0x22c3a439u, 0x2cd42582u, 0x2b35b402u, 0x29684861u,
    0x2ca8ba64u, 0x26185d03u, 0x3015d9ccu, 0x2f2235d5u, 0x0e4989f4u, 0x08952cd4u, 0x28f89973u, 0x0ac93c16u,
    0x3082c480u, 0x06154b2bu, 0x00871e8au, 0x125ad037u, 0x1b9c1e8au, 0x25848a71u, 0x1c37a5a2u, 0x2e332311u,
    0x1f7b6408u, 0x010c9131u, 0x04d8162fu, 0x2a63da4eu, 0x05462ae3u, 0x0a7bad43u, 0x20c33967u, 0x265cb8ccu
  }};
  int grid = num_sms;
  const int min_grid = (B + kMaxB - 1) / kMaxB;
  if (grid < min_grid) grid = min_grid;
  if (grid > B) grid = B;
  afm_kernel<<<grid, kThreads, SMEM_BYTES>>>(idx, table, W, B / grid, B % grid, B * kF - 2, ii, jj, bias, hvec, pvec,
                                             out, sched);
}
```

```cpp
#include <cuda_runtime.h>
#include <cuda_bf16.h>
#include <cuda_fp16.h>
#include <stdint.h>
#include <type_traits>

#define AFM_MAXFORM 1
#define AFM_WPFN 32
#define AFM_RC 216
#define AFM_SPLIT1 2
#define AFM_LPF 1
#define AFM_GINL __noinline__
#define AFM_POLL 200
#define AFM_HINT 20000
#define AFM_G1DELAY 200
#define AFM_HSLEEP 300
namespace {

constexpr int kF = 26;
constexpr int kD = 128;
constexpr int kP = 325;
constexpr int kMaxB = 8;
constexpr int kThreads = 384;
constexpr int kRow = 320;
constexpr int kElem = kF * kRow;

constexpr int B_NBLK = 16 * 1024;
constexpr int OFF_B = 0;
constexpr int OFF_EMB = 2 * B_NBLK;
constexpr int OFF_ES = OFF_EMB + kMaxB * kElem;
constexpr int ES_STRIDE = 5 * 1024;
constexpr int OFF_VEC = OFF_ES + (kMaxB + 2) * ES_STRIDE;
constexpr int OFF_STAT = OFF_VEC + 768;
constexpr int OFF_BAR = OFF_STAT + 128;
constexpr int SMEM_USED = OFF_BAR + 128;
static_assert(OFF_EMB + (kMaxB + 2) * kElem <= SMEM_USED, "unused operand prefetches run up to 2 elements past the end");
constexpr int SMEM_BYTES = SMEM_USED;
static_assert(OFF_ES % 16 == 0 && OFF_VEC % 16 == 0 && OFF_STAT % 16 == 0 && kElem % 128 == 0, "alignment");

struct Sched { uint32_t e[32]; };
struct Late {
  const __nv_bfloat16* vec[4];
  const int* ii;
  const int* jj;
  __nv_bfloat16* out;
  Sched sched;
};

constexpr int kMaxChunk = 8192;
__device__ float2 g_left[kMaxChunk];

__device__ __forceinline__ uint32_t smem_u32(const void* p) { return (uint32_t)__cvta_generic_to_shared(p); }
__device__ __forceinline__ void named_bar_sync(int id, int n) { asm volatile("bar.sync %0, %1;" ::"r"(id), "r"(n) : "memory"); }
__device__ __forceinline__ void named_bar_arrive(int id, int n) { asm volatile("bar.arrive %0, %1;" ::"r"(id), "r"(n) : "memory"); }
template <int A, int B>
__device__ __forceinline__ void bar_sync2(uint32_t sel) {
  asm volatile("{\n.reg .pred p;\nsetp.eq.u32 p, %0, 0;\n@p bar.sync %1, 256;\n@!p bar.sync %2, 256;\n}" ::"r"(sel), "n"(A), "n"(B) : "memory");
}
template <int A, int B, int N = 256>
__device__ __forceinline__ void bar_arrive2(uint32_t sel) {
  asm volatile("{\n.reg .pred p;\nsetp.eq.u32 p, %0, 0;\n@p bar.arrive %1, %3;\n@!p bar.arrive %2, %3;\n}" ::"r"(sel), "n"(A), "n"(B), "n"(N) : "memory");
}
template <int A, int B, int N>
__device__ __forceinline__ void bar_arrive2p(uint32_t sel, bool on) {
  asm volatile("{\n.reg .pred p, q;\nsetp.ne.u32 q, %4, 0;\nsetp.eq.and.u32 p|q, %0, 0, q;\n@p bar.arrive %1, %3;\n@q bar.arrive %2, %3;\n}"
               ::"r"(sel), "n"(A), "n"(B), "n"(N), "r"((uint32_t)on) : "memory");
}
__device__ __forceinline__ void mbar_init(uint32_t bar, uint32_t count) {
  asm volatile("mbarrier.init.shared::cta.b64 [%0], %1;" ::"r"(bar), "r"(count) : "memory");
}
__device__ __forceinline__ void mbar_arrive(uint32_t bar) {
  asm volatile("mbarrier.arrive.shared::cta.b64 _, [%0];" ::"r"(bar) : "memory");
}
__device__ __forceinline__ void mbar_arrive_p(uint32_t bar, bool on) {
  asm volatile("{\n.reg .pred p;\nsetp.ne.u32 p, %1, 0;\n@p mbarrier.arrive.shared::cta.b64 _, [%0];\n}" ::"r"(bar), "r"((uint32_t)on) : "memory");
}
__device__ __forceinline__ uint32_t mbar_test(uint32_t bar, uint32_t parity) {
  uint32_t ok;
  asm volatile("{\n.reg .pred p;\nmbarrier.test_wait.parity.shared::cta.b64 p, [%1], %2;\nselp.u32 %0, 1, 0, p;\n}\n"
               : "=r"(ok) : "r"(bar), "r"(parity) : "memory");
  return ok;
}
__device__ __forceinline__ void mbar_wait(uint32_t bar, uint32_t parity) {
  uint32_t ok, it = 0;
  do {
    asm volatile("{\n.reg .pred p;\nmbarrier.try_wait.parity.shared::cta.b64 p, [%1], %2, %3;\nselp.u32 %0, 1, 0, p;\n}\n"
                 : "=r"(ok) : "r"(bar), "r"(parity), "r"(AFM_HINT) : "memory");
  } while (!ok && ++it < (1u << 16));
}
__device__ __forceinline__ void wgmma_fence() { asm volatile("wgmma.fence.sync.aligned;" ::: "memory"); }
__device__ __forceinline__ void wgmma_commit() { asm volatile("wgmma.commit_group.sync.aligned;" ::: "memory"); }
template <int N>
__device__ __forceinline__ void wgmma_wait() { asm volatile("wgmma.wait_group.sync.aligned %0;" ::"n"(N) : "memory"); }
__device__ __forceinline__ void fence_proxy_async() { asm volatile("fence.proxy.async.shared::cta;" ::: "memory"); }

__device__ __forceinline__ uint32_t hmul2(uint32_t a, uint32_t b) {
  uint32_t d;
  asm("mul.rn.f16x2 %0, %1, %2;" : "=r"(d) : "r"(a), "r"(b));
  return d;
}
__device__ __forceinline__ uint32_t hadd2(uint32_t a, uint32_t b) {
  uint32_t d;
  asm("add.rn.f16x2 %0, %1, %2;" : "=r"(d) : "r"(a), "r"(b));
  return d;
}
__device__ __forceinline__ uint32_t hfma2(uint32_t a, uint32_t b, uint32_t c) {
  uint32_t d;
  asm("fma.rn.f16x2 %0, %1, %2, %3;" : "=r"(d) : "r"(a), "r"(b), "r"(c));
  return d;
}
__device__ __forceinline__ uint32_t bias_relu2(uint32_t x, uint32_t nb) {
  uint32_t d;
  asm("max.NaN.f16x2 %0, %1, %2;" : "=r"(d) : "r"(x), "r"(nb));
  return d;
}
__device__ __forceinline__ uint32_t habsmax2(uint32_t a, uint32_t b) {
  uint32_t d;
  asm("max.NaN.xorsign.abs.f16x2 %0, %1, %2;" : "=r"(d) : "r"(a), "r"(b));
  return d;
}
__device__ __forceinline__ uint32_t babsmax2(uint32_t a, uint32_t b) {
  uint32_t d;
  asm("max.NaN.xorsign.abs.bf16x2 %0, %1, %2;" : "=r"(d) : "r"(a), "r"(b));
  return d;
}
__device__ __forceinline__ uint32_t hmax2(uint32_t a, uint32_t b) {
  uint32_t d;
  asm("max.f16x2 %0, %1, %2;" : "=r"(d) : "r"(a), "r"(b));
  return d;
}
__device__ __forceinline__ uint32_t bf2h(uint32_t x) {
  uint32_t d;
  asm("cvt.rn.f16x2.f32 %0, %1, %2;" : "=r"(d) : "f"(__uint_as_float(x & 0xffff0000u)), "f"(__uint_as_float(x << 16)));
  return d;
}
__device__ __forceinline__ uint32_t bf2h_x16(uint32_t x) {
  uint32_t hi, lo, d;
  asm("fma.rn.bf16x2 %0, %1, %2, %3;" : "=r"(hi) : "r"(x), "r"(0x41800000u), "r"(0u));
  asm("{\n.reg .b16 l, h;\n.reg .b32 t;\nmov.b32 {l, h}, %1;\nmov.b32 t, {l, l};\nfma.rn.bf16x2 %0, t, %2, %3;\n}"
      : "=r"(lo) : "r"(x), "r"(0x41800000u), "r"(0u));
  asm("cvt.rn.f16x2.f32 %0, %1, %2;" : "=r"(d) : "f"(__uint_as_float(hi)), "f"(__uint_as_float(lo)));
  return d;
}
__device__ __forceinline__ uint4 convert(uint4 v) { return make_uint4(bf2h(v.x), bf2h(v.y), bf2h(v.z), bf2h(v.w)); }
__device__ __forceinline__ float h_lo(uint32_t x) { return __half2float(__ushort_as_half((unsigned short)(x & 0xffffu))); }
__device__ __forceinline__ float h_hi(uint32_t x) { return __half2float(__ushort_as_half((unsigned short)(x >> 16))); }
__device__ __forceinline__ uint32_t redux_max(uint32_t v) {
  uint32_t d;
  asm volatile("redux.sync.max.u32 %0, %1, 0xffffffff;" : "=r"(d) : "r"(v));
  return d;
}
__device__ __forceinline__ uint32_t absmax_bits(uint32_t m) { return max(m & 0x7fffu, (m >> 16) & 0x7fffu); }

template <int OFF>
__device__ __forceinline__ uint4 lds128(uint32_t addr) {
  uint4 v;
  asm volatile("ld.shared.v4.u32 {%0,%1,%2,%3}, [%4+%5];" : "=r"(v.x), "=r"(v.y), "=r"(v.z), "=r"(v.w) : "r"(addr), "n"(OFF));
  return v;
}
template <int OFF>
__device__ __forceinline__ void sts128(uint32_t addr, uint4 v) {
  asm volatile("st.shared.v4.u32 [%0+%5], {%1,%2,%3,%4};" ::"r"(addr), "r"(v.x), "r"(v.y), "r"(v.z), "r"(v.w), "n"(OFF) : "memory");
}
__device__ __forceinline__ uint32_t lds32(uint32_t addr) {
  uint32_t v;
  asm volatile("ld.shared.u32 %0, [%1];" : "=r"(v) : "r"(addr));
  return v;
}
__device__ __forceinline__ void sts32(uint32_t addr, uint32_t v) { asm volatile("st.shared.u32 [%0], %1;" ::"r"(addr), "r"(v) : "memory"); }
__device__ __forceinline__ uint32_t ldg32(const void* p) {
  uint32_t v;
  asm volatile("ld.global.u32 %0, [%1];" : "=r"(v) : "l"(p) : "memory");
  return v;
}
__device__ __forceinline__ uint4 ldg128(const void* p) {
  uint4 v;
  asm volatile("ld.global.v4.u32 {%0,%1,%2,%3}, [%4];" : "=r"(v.x), "=r"(v.y), "=r"(v.z), "=r"(v.w) : "l"(p) : "memory");
  return v;
}
__device__ __forceinline__ uint2 ldg64(const void* p) {
  uint2 v;
  asm volatile("ld.global.v2.u32 {%0,%1}, [%2];" : "=r"(v.x), "=r"(v.y) : "l"(p) : "memory");
  return v;
}
__device__ __forceinline__ uint2 ldg64p(const void* p, bool on) {
  uint2 v;
  asm volatile("{\n.reg .pred p;\nsetp.ne.u32 p, %3, 0;\n@p ld.volatile.global.v2.u32 {%0,%1}, [%2];\n}" : "=r"(v.x), "=r"(v.y) : "l"(p), "r"((uint32_t)on) : "memory");
  return v;
}
__device__ __forceinline__ uint4 ldg128p(const void* p, bool on) {
  uint4 v = make_uint4(0u, 0u, 0u, 0u);
  asm volatile("{\n.reg .pred p;\nsetp.ne.u32 p, %5, 0;\n@p ld.global.v4.u32 {%0,%1,%2,%3}, [%4];\n}"
               : "+r"(v.x), "+r"(v.y), "+r"(v.z), "+r"(v.w) : "l"(p), "r"((uint32_t)on) : "memory");
  return v;
}
__device__ __forceinline__ uint4 ldg_row(const void* base, uint32_t row, bool on) {
  uint4 v;
  asm volatile("{\n.reg .pred p;\n.reg .b64 a;\nsetp.ne.u32 p, %6, 0;\nmad.wide.u32 a, %5, 256, %4;\n@p ld.global.v4.u32 {%0,%1,%2,%3}, [a];\n}"
               : "=r"(v.x), "=r"(v.y), "=r"(v.z), "=r"(v.w) : "l"(base), "r"(row), "r"((uint32_t)on) : "memory");
  return v;
}
template <int OFF>
__device__ __forceinline__ uint4 lds128p(uint32_t addr, bool on) {
  uint4 v;
  asm volatile("{\n.reg .pred p;\nsetp.ne.u32 p, %6, 0;\n@p ld.shared.v4.u32 {%0,%1,%2,%3}, [%4+%5];\n}"
               : "=r"(v.x), "=r"(v.y), "=r"(v.z), "=r"(v.w) : "r"(addr), "n"(OFF), "r"((uint32_t)on));
  return v;
}
template <int OFF>
__device__ __forceinline__ void sts128p(uint32_t addr, uint4 v, bool on) {
  asm volatile("{\n.reg .pred p;\nsetp.ne.u32 p, %6, 0;\n@p st.shared.v4.u32 [%0+%5], {%1,%2,%3,%4};\n}"
               ::"r"(addr), "r"(v.x), "r"(v.y), "r"(v.z), "r"(v.w), "n"(OFF), "r"((uint32_t)on) : "memory");
}
__device__ __forceinline__ void sts32p(uint32_t addr, uint32_t v, bool on) {
  asm volatile("{\n.reg .pred p;\nsetp.ne.u32 p, %2, 0;\n@p st.shared.u32 [%0], %1;\n}" ::"r"(addr), "r"(v), "r"((uint32_t)on) : "memory");
}
__device__ __forceinline__ void pin2(uint32_t a, uint32_t b, uint32_t never) {
  asm volatile("{\n.reg .pred p;\nsetp.ne.u32 p, %2, 0;\n@p st.shared.u32 [%0], %1;\n}" ::"r"(a), "r"(b), "r"(never) : "memory");
}
__device__ __forceinline__ uint32_t shfl_xor_v(uint32_t v, int m) {
  uint32_t d;
  asm volatile("shfl.sync.bfly.b32 %0, %1, %2, 0x1f, 0xffffffff;" : "=r"(d) : "r"(v), "r"(m));
  return d;
}
template <int M>
__device__ __forceinline__ uint32_t shfl_xor(uint32_t v) {
  uint32_t d;
  asm volatile("shfl.sync.bfly.b32 %0, %1, %2, 0x1f, 0xffffffff;" : "=r"(d) : "r"(v), "n"(M));
  return d;
}
template <int I, int N, typename F>
__device__ __forceinline__ void static_for(F&& f) {
  if constexpr (I < N) {
    f(std::integral_constant<int, I>{});
    static_for<I + 1, N>(f);
  }
}
template <int N>
__device__ __forceinline__ void fence_regs(uint32_t (&r)[N]) {
#pragma unroll
  for (int i = 0; i < N; i++) asm volatile("" : "+r"(r[i])::"memory");
}
__device__ __forceinline__ void load_vec(uint32_t (&v)[16], uint32_t a) {
  const uint4 v0 = lds128<0>(a), v1 = lds128<64>(a), v2 = lds128<128>(a), v3 = lds128<192>(a);
  v[0] = v0.x; v[1] = v0.y; v[2] = v0.z; v[3] = v0.w; v[4] = v1.x; v[5] = v1.y; v[6] = v1.z; v[7] = v1.w;
  v[8] = v2.x; v[9] = v2.y; v[10] = v2.z; v[11] = v2.w; v[12] = v3.x; v[13] = v3.y; v[14] = v3.z; v[15] = v3.w;
}

__device__ __forceinline__ void load_vec_p(uint32_t (&v)[16], uint32_t a, bool on) {
  asm volatile("{\n.reg .pred p;\nsetp.ne.u32 p, %17, 0;\n"
               "@p ld.shared.v4.u32 {%0,%1,%2,%3}, [%16];\n@p ld.shared.v4.u32 {%4,%5,%6,%7}, [%16+64];\n"
               "@p ld.shared.v4.u32 {%8,%9,%10,%11}, [%16+128];\n@p ld.shared.v4.u32 {%12,%13,%14,%15}, [%16+192];\n}"
               : "+r"(v[0]), "+r"(v[1]), "+r"(v[2]), "+r"(v[3]), "+r"(v[4]), "+r"(v[5]), "+r"(v[6]), "+r"(v[7]), "+r"(v[8]),
                 "+r"(v[9]), "+r"(v[10]), "+r"(v[11]), "+r"(v[12]), "+r"(v[13]), "+r"(v[14]), "+r"(v[15])
               : "r"(a), "r"((uint32_t)on));
}
template <int OFF>
__device__ __forceinline__ void sts32o(uint32_t addr, uint32_t v) {
  asm volatile("st.shared.u32 [%0+%2], %1;" ::"r"(addr), "r"(v), "n"(OFF) : "memory");
}
__device__ __forceinline__ void keep2(uint32_t& ck, uint32_t a, uint32_t b, uint32_t never) {
  asm volatile("{\n.reg .pred p;\nsetp.ne.u32 p, %3, 0;\n@p xor.b32 %0, %1, %2;\n}" : "+r"(ck) : "r"(a), "r"(b), "r"(never));
}
__device__ __forceinline__ float exp_e(uint32_t es) {
  float w;
  asm("ex2.approx.ftz.f32 %0, %1;" : "=f"(w) : "f"(h_lo(es) * (1.4426950408889634f / 256.f)));
  return w;
}
__device__ __forceinline__ uint32_t clock32() {
  uint32_t v;
  asm volatile("mov.u32 %0, %%clock;" : "=r"(v)::"memory");
  return v;
}
__device__ __forceinline__ void sched_fence(uint32_t& ck, uint32_t never) {
  asm volatile("{\n.reg .pred p;\nsetp.ne.u32 p, %1, 0;\n@p mov.u32 %0, %%clock;\n}" : "+r"(ck) : "r"(never) : "memory");
}

template <int ACCUM>
__device__ __forceinline__ void wgmma_rs_n128(uint32_t (&d)[32], uint32_t a0, uint32_t a1, uint32_t a2, uint32_t a3, uint64_t descB) {
  if (ACCUM == 1) {
    asm volatile(
        "wgmma.mma_async.sync.aligned.m64n128k16.f16.f16.f16 "
        "{%0, %1, %2, %3, %4, %5, %6, %7, %8, %9, %10, %11, %12, %13, %14, %15, %16, %17, %18, %19, %20, %21, %22, %23, %24, %25, %26, %27, %28, %29, %30, %31}, "
        "{%32, %33, %34, %35}, %36, 1, 1, 1, 1;\n"
        : "+r"(d[0]), "+r"(d[1]), "+r"(d[2]), "+r"(d[3]), "+r"(d[4]), "+r"(d[5]), "+r"(d[6]), "+r"(d[7]), "+r"(d[8]), "+r"(d[9]), "+r"(d[10]), "+r"(d[11]), "+r"(d[12]), "+r"(d[13]), "+r"(d[14]), "+r"(d[15]), "+r"(d[16]), "+r"(d[17]), "+r"(d[18]), "+r"(d[19]), "+r"(d[20]), "+r"(d[21]), "+r"(d[22]), "+r"(d[23]), "+r"(d[24]), "+r"(d[25]), "+r"(d[26]), "+r"(d[27]), "+r"(d[28]), "+r"(d[29]), "+r"(d[30]), "+r"(d[31])
        : "r"(a0), "r"(a1), "r"(a2), "r"(a3), "l"(descB));
  }
  if (ACCUM == 0) {
    asm volatile(
        "wgmma.mma_async.sync.aligned.m64n128k16.f16.f16.f16 "
        "{%0, %1, %2, %3, %4, %5, %6, %7, %8, %9, %10, %11, %12, %13, %14, %15, %16, %17, %18, %19, %20, %21, %22, %23, %24, %25, %26, %27, %28, %29, %30, %31}, "
        "{%32, %33, %34, %35}, %36, 0, 1, 1, 1;\n"
        : "=r"(d[0]), "=r"(d[1]), "=r"(d[2]), "=r"(d[3]), "=r"(d[4]), "=r"(d[5]), "=r"(d[6]), "=r"(d[7]), "=r"(d[8]), "=r"(d[9]), "=r"(d[10]), "=r"(d[11]), "=r"(d[12]), "=r"(d[13]), "=r"(d[14]), "=r"(d[15]), "=r"(d[16]), "=r"(d[17]), "=r"(d[18]), "=r"(d[19]), "=r"(d[20]), "=r"(d[21]), "=r"(d[22]), "=r"(d[23]), "=r"(d[24]), "=r"(d[25]), "=r"(d[26]), "=r"(d[27]), "=r"(d[28]), "=r"(d[29]), "=r"(d[30]), "=r"(d[31])
        : "r"(a0), "r"(a1), "r"(a2), "r"(a3), "l"(descB));
  }
}
__device__ __forceinline__ void wgmma_rs_n128_p(uint32_t (&d)[32], uint32_t a0, uint32_t a1, uint32_t a2, uint32_t a3, uint64_t descB, uint32_t accum) {
  asm volatile(
      "{\n.reg .pred p;\nsetp.ne.u32 p, %37, 0;\n"
      "wgmma.mma_async.sync.aligned.m64n128k16.f16.f16.f16 "
      "{%0, %1, %2, %3, %4, %5, %6, %7, %8, %9, %10, %11, %12, %13, %14, %15, %16, %17, %18, %19, %20, %21, %22, %23, %24, %25, %26, %27, %28, %29, %30, %31}, "
      "{%32, %33, %34, %35}, %36, p, 1, 1, 1;\n}\n"
      : "+r"(d[0]), "+r"(d[1]), "+r"(d[2]), "+r"(d[3]), "+r"(d[4]), "+r"(d[5]), "+r"(d[6]), "+r"(d[7]), "+r"(d[8]), "+r"(d[9]), "+r"(d[10]), "+r"(d[11]), "+r"(d[12]), "+r"(d[13]), "+r"(d[14]), "+r"(d[15]), "+r"(d[16]), "+r"(d[17]), "+r"(d[18]), "+r"(d[19]), "+r"(d[20]), "+r"(d[21]), "+r"(d[22]), "+r"(d[23]), "+r"(d[24]), "+r"(d[25]), "+r"(d[26]), "+r"(d[27]), "+r"(d[28]), "+r"(d[29]), "+r"(d[30]), "+r"(d[31])
      : "r"(a0), "r"(a1), "r"(a2), "r"(a3), "l"(descB), "r"(accum));
}

#define TL(slot) sched_fence(ck, never)
#define TLL(off) sched_fence(ck, never)
#define TLX(off)
#define TLS()

#define TH(slot)
__device__ __forceinline__ float rbf(float x) { return __bfloat162float(__float2bfloat16_rn(x)); }
__device__ __forceinline__ float warp_sum(float v) {
#pragma unroll
  for (int o = 16; o > 0; o >>= 1) v += __shfl_xor_sync(0xffffffffu, v, o);
  return v;
}

__device__ AFM_GINL void general_element(const int* __restrict__ idx, const __nv_bfloat16* __restrict__ table,
                                             const int* __restrict__ ii, const int* __restrict__ jj,
                                             const __nv_bfloat16* __restrict__ W, const __nv_bfloat16* __restrict__ bias,
                                             const __nv_bfloat16* __restrict__ hvec, const __nv_bfloat16* __restrict__ pvec,
                                             __nv_bfloat16* __restrict__ out, float* ev) {
  const int lane = threadIdx.x & 31;
  auto pair4 = [&](int p, float (&pr)[4]) {
    const __nv_bfloat16* a = table + (size_t)idx[ii[p]] * kD + 4 * lane;
    const __nv_bfloat16* b = table + (size_t)idx[jj[p]] * kD + 4 * lane;
#pragma unroll
    for (int q = 0; q < 4; q++) pr[q] = rbf(__bfloat162float(a[q]) * __bfloat162float(b[q]));
  };
  float m = -INFINITY;
  bool has_nan = false;
  for (int p = 0; p < kP; p++) {
    float pr[4], x[4] = {0.f, 0.f, 0.f, 0.f};
    pair4(p, pr);
    for (int l = 0; l < 32; l++) {
#pragma unroll
      for (int q = 0; q < 4; q++) {
        const float v = __shfl_sync(0xffffffffu, pr[q], l);
        const uint2 w = *reinterpret_cast<const uint2*>(W + (4 * l + q) * kD + 4 * lane);
        x[0] = fmaf(v, __uint_as_float(w.x << 16), x[0]);
        x[1] = fmaf(v, __uint_as_float(w.x & 0xffff0000u), x[1]);
        x[2] = fmaf(v, __uint_as_float(w.y << 16), x[2]);
        x[3] = fmaf(v, __uint_as_float(w.y & 0xffff0000u), x[3]);
      }
    }
    float e = 0.f;
#pragma unroll
    for (int q = 0; q < 4; q++) {
      const float y = rbf(rbf(x[q]) + __bfloat162float(bias[4 * lane + q]));
      e = fmaf(rbf(0.5f * rbf(y + fabsf(y))), __bfloat162float(hvec[4 * lane + q]), e);
    }
    e = rbf(warp_sum(e));
    has_nan |= (e != e);
    m = fmaxf(m, e);
    if (lane == 0) ev[p] = e;
  }
  __syncwarp();
  float l = 0.f;
  for (int p = lane; p < kP; p += 32) l += expf(ev[p] - m);
  l = warp_sum(l);
  float pooled[4] = {0.f, 0.f, 0.f, 0.f};
  for (int p = 0; p < kP; p++) {
    float pr[4];
    pair4(p, pr);
    const float al = rbf(expf(ev[p] - m) / l);
#pragma unroll
    for (int q = 0; q < 4; q++) pooled[q] = fmaf(al, pr[q], pooled[q]);
  }
  float o = 0.f;
#pragma unroll
  for (int q = 0; q < 4; q++) o = fmaf(rbf(pooled[q]), __bfloat162float(pvec[4 * lane + q]), o);
  o = warp_sum(o);
  if (has_nan) o = __int_as_float(0x7fffffff);
  if (lane == 0) *out = __float2bfloat16_rn(o);
}

__device__ __forceinline__ void helper_rest(const int* __restrict__ idx, const __nv_bfloat16* __restrict__ table,
                                            const __nv_bfloat16* __restrict__ W, const Late& late, int base_cnt, int extra,
                                            int last_row, int n_left, uint8_t* smem) {
  constexpr uint32_t sbase = 0x400u;
  uint32_t tid, cta;
  asm volatile("mov.u32 %0, %%tid.x;\nmov.u32 %1, %%ctaid.x;" : "=r"(tid), "=r"(cta));
  const int t = tid & 127, lane = tid & 31, wq = (tid >> 5) & 3;
  cta -= n_left;
  const int n_out = base_cnt + ((int)cta < extra ? 1 : 0), n_c = max(n_out, 2);
  const int b0 = cta * base_cnt + min((int)cta, extra);
  const int grp = 7 - (t >> 4);
  const bool v01 = grp < 7, v23 = grp < 6;
  int irow = (b0 + (n_c > 2 ? 2 : 0)) * kF + 4 * grp;
  uint2 gi01 = ldg64(idx + min(irow, last_row));
  uint2 gi23 = ldg64(idx + min(irow + 2, last_row));
  const __nv_bfloat16* gsrc = table + (t & 15) * 8;
  uint32_t cv_ptr = sbase + OFF_EMB + 2 * kElem + 4 * grp * kRow + (t & 15) * 16;
  uint32_t me = 0, ck = 0;
  auto track = [&](const uint4& a, const uint4& b, bool on) {
    const uint32_t m = babsmax2(babsmax2(babsmax2(a.x, a.y), babsmax2(a.z, a.w)), babsmax2(babsmax2(b.x, b.y), babsmax2(b.z, b.w)));
    me = babsmax2(me, on ? m : 0u);
  };
  named_bar_sync(6, 160);
#pragma unroll 1
  for (int e = 2; e < n_c + 2; e++) {
    const uint4 g0 = ldg_row(gsrc, gi01.x, v01), g1 = ldg_row(gsrc, gi01.y, v01);
    const uint4 g2 = ldg_row(gsrc, gi23.x, v23), g3 = ldg_row(gsrc, gi23.y, v23);
    irow += e + 1 == n_c ? (1 - n_c) * kF : kF;
    gi01 = ldg64(idx + min(irow, last_row));
    gi23 = ldg64(idx + min(irow + 2, last_row));
    uint4 h0 = convert(g0), h1 = convert(g1), h2 = convert(g2), h3 = convert(g3);
    asm volatile("" : "+r"(h0.x), "+r"(h0.y), "+r"(h0.z), "+r"(h0.w), "+r"(h1.x), "+r"(h1.y), "+r"(h1.z), "+r"(h1.w),
                      "+r"(h2.x), "+r"(h2.y), "+r"(h2.z), "+r"(h2.w), "+r"(h3.x), "+r"(h3.y), "+r"(h3.z), "+r"(h3.w));
    sched_fence(ck, tid >> 10);
    sts128p<0>(cv_ptr, h0, v01 && e < n_c);
    sts128p<kRow>(cv_ptr, h1, v01 && e < n_c);
    sts128p<2 * kRow>(cv_ptr, h2, v23 && e < n_c);
    sts128p<3 * kRow>(cv_ptr, h3, v23 && e < n_c);
    __syncwarp();
    mbar_arrive_p(sbase + OFF_BAR + 8 * e, lane == 0 && e < n_c);
    sched_fence(ck, tid >> 10);
    cv_ptr += kElem;
    track(g0, g1, v01);
    track(g2, g3, v23);
    if (AFM_HSLEEP && e >= 3 && e < n_c) {
      __nanosleep(AFM_HSLEEP);
    }
  }
  TH(7);
  bool ok_cta;
  float ds;
  {
    const uint32_t s0 = ldg32(late.vec[t >> 6] + 2 * (t & 63)), s1 = ldg32(late.vec[2] + 2 * (t & 63));
    uint32_t pi[3], pj[3];
#pragma unroll
    for (int r = 0; r < 3; r++) {
      pi[r] = ldg32(late.ii + min(t + 128 * r, kP - 1));
      pj[r] = ldg32(late.jj + min(t + 128 * r, kP - 1));
    }
    float v0 = 16.f * (fabsf(__uint_as_float(s0 << 16)) + fabsf(__uint_as_float(s0 & 0xffff0000u)));
    float v1 = 16.f * (fabsf(__uint_as_float(s1 << 16)) + fabsf(__uint_as_float(s1 & 0xffff0000u)));
    bool good = true;
#pragma unroll
    for (int r = 0; r < 3; r++)
      good &= (pi[r] < pj[r]) & (pj[r] < kF) & (((pi[r] * (2 * kF - 1 - pi[r])) >> 1) + pj[r] - pi[r] - 1 == min(t + 128 * r, kP - 1));
    if (!good) v0 = __int_as_float(0x7fffffff);
    v0 = warp_sum(v0);
    v1 = warp_sum(v1);
    sts32p(sbase + OFF_STAT + 64 + wq * 4, __float_as_uint(v0), lane == 0);
    sts32p(sbase + OFF_STAT + 80 + wq * 4, __float_as_uint(v1), lane == 0);
    sts32p(sbase + OFF_STAT + 16 + wq * 4 + ck, redux_max(absmax_bits(me)), lane == 0);
    named_bar_sync(6, 128);
    const uint32_t st = lds32(sbase + OFF_STAT + lane * 4);
    const float Wm = 2048.f * __uint_as_float(redux_max(lane < 4 ? st : 0u) << 16);
    const float M = __uint_as_float(redux_max(lane >= 4 && lane < 8 ? st : 0u) << 16);
    const float sp = __uint_as_float(st) + __shfl_xor_sync(0xffffffffu, __uint_as_float(st), 1);
    const float Bs = __shfl_sync(0xffffffffu, sp, 16);
    const float Hs = __shfl_sync(0xffffffffu, sp, 18);
    const float Ps = __shfl_sync(0xffffffffu, sp, 20);
    const float M2 = M * M, X = fmaf(M2, Wm, Bs), G = fmaf(2.f, M, 1.f);
    constexpr float u = 1.f / 33554432.f;
    const float de = u * (Hs * (Wm * G + 128.f * M2 + 16.f) + 128.f * X + 256.f);
    ds = u * (Ps * G + 128.f * M2 + 256.f);
    ok_cta = M2 <= 60000.f && Wm <= 128.f * 60000.f && X <= 60000.f && Hs <= 60000.f && Ps <= 60000.f && de <= 1.f;
  }
  TH(8);
  float pl = 1.f, pa = 0.f;
#pragma unroll 1
  for (int e = wq; e < n_c; e += 4) {
    const uint32_t ea = sbase + OFF_ES + (2 + e) * ES_STRIDE + lane * 16;
    float l = 0.f, a = 0.f;
    uint32_t mx = 0;
    auto take = [&](const uint4& v) {
      const uint32_t es = hadd2(hadd2(v.x, v.y), hadd2(v.z, v.w));
      const float w = exp_e(es);
      mx = habsmax2(mx, es);
      l += w;
      a = fmaf(w, h_hi(es), a);
    };
    const bool last = e + 2 >= n_c;
    if (last) named_bar_sync(2 + (e & 1), 160);
    else mbar_wait(sbase + OFF_BAR + 80 + 8 * e, 0);
    {
      uint4 v[6];
      static_for<0, 6>([&](auto Qc) { v[decltype(Qc)::value] = lds128<decltype(Qc)::value * 512>(ea); });
      sched_fence(ck, tid >> 10);
#pragma unroll
      for (int q = 0; q < 6; q++) take(v[q]);
    }
    if (e < 4) {
      if (lane < 2 && wq + 4 * lane < n_out) {
        float2* const gp = g_left + b0 + wq + 4 * lane;
        for (uint32_t it = 0; it < (1u << 22); it++) {
          asm volatile("ld.volatile.global.v2.f32 {%0,%1}, [%2];" : "=f"(pl), "=f"(pa) : "l"(gp) : "memory");
          if (__float_as_uint(pl) != 0u) break;
          __nanosleep(AFM_POLL);
        }
        asm volatile("st.volatile.global.v2.f32 [%0], {%1,%1};" ::"l"(gp), "f"(0.f) : "memory");
      }
      __syncwarp();
    }
    const bool mine = lane == (e >> 2);
    l += mine ? pl : 0.f;
    a += mine ? pa : 0.f;
    __nv_bfloat16* op = late.out + b0 + e;
    asm volatile("" : "+l"(op));
    TH(13);
    if (last) named_bar_sync(10 + (e & 1), 160);
    take(lds128<3072>(ea));
    take(lds128<3072 + 512>(ea));
    asm volatile("" : "+f"(l), "+f"(a), "+r"(mx));
    sched_fence(ck, tid >> 10);
    asm volatile("{\n.reg .pred p, q;\nsetp.ne.u32 q, %1, 0;\nsetp.eq.and.u32 p|q, %0, 0, q;\n@p bar.sync 8, 160;\n@q bar.sync 9, 160;\n}"
                 ::"r"(e & 1), "r"((uint32_t)last) : "memory");
    {
      const uint4 v0 = lds128<4096>(ea + ck), v1 = lds128<4096 + 512>(ea);
      take(v0);
      take(v1);
    }
    const uint32_t big = __ballot_sync(0xffffffffu, ds <= fabsf(h_hi(mx)) * (1.f / 16384.f));
    const uint32_t bad = __ballot_sync(0xffffffffu, ((mx & 0x7fffu) > 0x7000u) | ((mx & 0x7c000000u) == 0x7c000000u) | (mine & !(pl > 0.f)));
    const bool ok = (big != 0u) & (bad == 0u) & ok_cta;
#pragma unroll
    for (int o = 0; o < 5; o++) {
      l += __uint_as_float(shfl_xor_v(__float_as_uint(l), 1 << o));
      a += __uint_as_float(shfl_xor_v(__float_as_uint(a), 1 << o));
    }
    float r;
    asm("rcp.approx.ftz.f32 %0, %1;" : "=f"(r) : "f"(l));
    if (lane == 0 && e < n_out) *op = __float2bfloat16_rn(a * 0.0625f * r);
    TH(12);
    if (!ok && e < n_out)
      general_element(idx + (b0 + e) * kF, table, late.ii, late.jj, W, late.vec[0], late.vec[1], late.vec[2], op, reinterpret_cast<float*>(smem + OFF_EMB + e * kElem));
  }
  TH(9);
}

__global__ void __launch_bounds__(kThreads, 1)
afm_kernel(const int* __restrict__ idx, const __nv_bfloat16* __restrict__ table, const __nv_bfloat16* __restrict__ W,
           int base_cnt, int extra, int last_row, int n_left, const __grid_constant__ Late late) {
  extern __shared__ __align__(1024) uint8_t smem[];
  constexpr uint32_t sbase = 0x400u;

  const int tid = threadIdx.x;
  const int t = tid & 127;
  const int lane = tid & 31;
  const int warp = tid >> 5;
  uint32_t ck = 0;
  uint32_t never = tid >> 10;
  const int cta = max((int)blockIdx.x - n_left, 0);
  const int b0 = cta * base_cnt + min(cta, extra);
  const int grp = 7 - (t >> 4);
  const bool v01 = grp < 7, v23 = grp < 6;
  const bool is_left = (int)blockIdx.x < n_left;
  const int irow = (b0 + (tid >> 7)) * kF + 4 * grp;
  uint2 gi01 = ldg64p(idx + min(irow, last_row), tid < 256);
  uint2 gi23 = ldg64p(idx + min(irow + 2, last_row), tid < 256);
  asm volatile("{\n.reg .pred p;\nsetp.ge.u32 p, %1, %2;\n@p prefetch.global.L2 [%0];\n}" ::"l"(W + ((blockIdx.x * AFM_WPFN + tid) & 255) * 64), "r"(tid), "n"(384 - AFM_WPFN) : "memory");
  sched_fence(ck, never);
  TL(1);
  const int wq = warp & 3;
  const int wg = __shfl_sync(0xffffffffu, tid >> 7, 0);
  const int n_out = base_cnt + (cta < extra ? 1 : 0);
  const int n_c = max(n_out, 2);
  const __nv_bfloat16* gsrc = table + (t & 15) * 8;
  asm volatile("" : "+l"(gsrc));
  uint32_t cv_ptr = sbase + OFF_EMB + wg * kElem + 4 * grp * kRow + (t & 15) * 16;

  if (wg < 2) {
    const int c = lane & 3;
    const int tau = t >> 2;
    asm volatile("{\n.reg .pred p;\nsetp.lt.u32 p, %2, 192;\n@p cp.async.ca.shared.global [%0], [%1], 4;\ncp.async.commit_group;\n}"
                 ::"r"(sbase + OFF_ES + tid * 4), "l"(late.vec[tid >> 6] + 2 * (tid & 63)), "r"(tid) : "memory");
    if (warp == 7) {
      if (lane == 0) {
#pragma unroll
        for (int i = 0; i < 16; i++) mbar_init(sbase + OFF_BAR + 8 * i, i < 2 ? 1 : i < 8 ? 4 : 128);
        mbar_arrive(sbase + OFF_BAR);
        mbar_arrive(sbase + OFF_BAR + 8);
      }
      if (smem_u32(smem) != sbase) __trap();
      __syncwarp();
      named_bar_arrive(6, 160);
    }
    if (is_left) {
      const int* ip = idx + min((int)(blockIdx.x * 256 + (tid >> 2)) * kF, last_row + 2 - kF);
      gi01 = ldg64(ip);
      gi23 = ldg64(ip + 2);
    }
    const int nb = (n_c - wg + 1) >> 1;
    const uint32_t sc = late.sched.e[tau];
    uint4 g0[4];
    auto gather_first = [&]() {
      g0[0] = ldg_row(gsrc, gi01.x, v01 && !is_left);
      g0[1] = ldg_row(gsrc, gi01.y, v01 && !is_left);
      g0[2] = ldg_row(gsrc, gi23.x, v23 && !is_left);
      g0[3] = ldg_row(gsrc, gi23.y, v23 && !is_left);
    };
    TL(2);
    auto small_vectors = [&]() {
      asm volatile("cp.async.wait_group 0;" ::: "memory");
      sts32p(sbase + OFF_VEC + (tid < 128 ? ((tid & 112u) | ((tid & 3u) << 2) | ((tid >> 2) & 3u)) : tid) * 4,
             bf2h_x16(lds32(sbase + OFF_ES + tid * 4)) ^ (AFM_MAXFORM && tid < 64 ? 0x80008000u : 0u), tid < 192);
    };
    if (wg == 1) {
      uint32_t y;
      asm volatile("or.b32 %0, %1, %2;" : "=r"(y) : "r"(gi01.x), "r"(gi23.x));
      const uint32_t t0 = clock32() + (y >> 31);
      while (clock32() - t0 < AFM_G1DELAY) {
      }
    }
    sched_fence(ck, never);
    gather_first();
    TL(3);
    small_vectors();
    named_bar_sync(1, 256);
    TL(5);
    uint32_t bs[16], hs[16], ps[16];
    load_vec(ps, sbase + OFF_VEC + 512 + c * 16);
    load_vec(bs, sbase + OFF_VEC + c * 16);
    load_vec(hs, sbase + OFF_VEC + 256 + c * 16);
    TL(4);
    if (is_left) {
      const uint32_t row = (c & 2) ? ((c & 1) ? gi23.y : gi23.x) : ((c & 1) ? gi01.y : gi01.x);
      asm volatile("prefetch.global.L2 [%0];\nprefetch.global.L2 [%0+128];" ::"l"(table + (size_t)row * kD) : "memory");
    }
    if (wg == 1) named_bar_sync(7, 256);
    asm volatile("setmaxnreg.inc.sync.aligned.u32 %0;" ::"n"(AFM_RC));
    if (wg == 0) named_bar_arrive(7, 256);
    uint32_t pt_ptr = shfl_xor<0>(sbase + OFF_ES + (2 + wg) * ES_STRIDE + t * 4);
    never = pt_ptr >> 31;
    uint32_t ra[6];
#pragma unroll
    for (int r = 0; r < 6; r++) ra[r] = sbase + OFF_EMB + wg * kElem + c * 16 + ((sc >> (5 * r)) & 31u) * kRow;
    asm volatile("" : "+r"(ra[0]), "+r"(ra[1]), "+r"(ra[2]), "+r"(ra[3]), "+r"(ra[4]), "+r"(ra[5]));
    TL(6);
    uint32_t Af[32], acc[32], S0[16], S1[16], S2[16], S3[16];
    constexpr uint64_t dB = (uint64_t)(((sbase + OFF_B) & 0x3FFFFu) >> 4) | ((uint64_t)(B_NBLK >> 4) << 16) |
                            ((uint64_t)(1024 >> 4) << 32) | ((uint64_t)1 << 62);
    auto products = [&](const uint32_t (&X)[16], const uint32_t (&Y)[16], const uint32_t (&Z)[16]) {
#pragma unroll
      for (int i = 0; i < 16; i++) {
        Af[2 * i] = hmul2(X[i], Z[i]);
        Af[2 * i + 1] = hmul2(Y[i], Z[i]);
      }
    };
    auto mma_tile = [&]() {
      fence_regs(Af);
      wgmma_fence();
#pragma unroll
      for (int s = 0; s < 8; s++) {
        const uint64_t d = dB + (uint64_t)(s * (2048 >> 4));
        if (s == 0) wgmma_rs_n128<0>(acc, Af[0], Af[1], Af[2], Af[3], d);
        else wgmma_rs_n128<1>(acc, Af[4 * s], Af[4 * s + 1], Af[4 * s + 2], Af[4 * s + 3], d);
      }
      wgmma_commit();
    };
    auto issue = [&]() {
      mma_tile();
      bar_arrive2<5, 4>(wg);
    };
    uint32_t eh0 = 0, eh1 = 0, sh0 = 0, sh1 = 0;
    auto fold = [&]() {
      eh0 = hadd2(__byte_perm(eh0, sh0, 0x5410), __byte_perm(eh0, sh0, 0x7632));
      eh1 = hadd2(__byte_perm(eh1, sh1, 0x5410), __byte_perm(eh1, sh1, 0x7632));
    };
    auto s_chain = [&]() {
      sh0 = hmul2(Af[0], ps[0]);
      sh1 = hmul2(Af[1], ps[0]);
#pragma unroll
      for (int i = 1; i < 16; i++) {
        sh0 = hfma2(Af[2 * i], ps[i], sh0);
        sh1 = hfma2(Af[2 * i + 1], ps[i], sh1);
      }
      asm volatile("" : "+r"(sh0), "+r"(sh1)::"memory");
    };
    auto epilogue = [&]() {
      wgmma_wait<0>();
      fence_regs(acc);
      fence_regs(S0); fence_regs(S1); fence_regs(S2); fence_regs(S3);
      TLX(12);
      eh0 = hmul2(bias_relu2(acc[0], bs[0]), hs[0]);
      eh1 = hmul2(bias_relu2(acc[1], bs[0]), hs[0]);
#pragma unroll
      for (int i = 1; i < 16; i++) {
        eh0 = hfma2(bias_relu2(acc[2 * i], bs[i]), hs[i], eh0);
        eh1 = hfma2(bias_relu2(acc[2 * i + 1], bs[i]), hs[i], eh1);
      }
      asm volatile("" : "+r"(eh0), "+r"(eh1)::"memory");
    };
    if (is_left) {
      if (wg == 1) named_bar_arrive(4, 256);
      const int n_elem = (last_row + 2) / kF;
      const __nv_bfloat16* lsrc = table + c * 8;
      uint32_t ia, ib, ic, id, ma;
      float lsum = 0.f, asum = 0.f;
      auto load_ix = [&](int r) {
        const int* ip = idx + min((int)blockIdx.x * 256 + (2 * r + wg) * 32 + tau, n_elem - 1) * kF;
        static_assert(0 == 0 && 1 == 1 && 2 == 2 && 3 == 3, "leftover fields");
        const uint2 x = ldg64(ip), y = ldg64(ip + 2);
        ia = x.x; ib = x.y; ic = y.x; id = y.y;
      };
      auto load_row = [&](uint32_t (&v)[16], uint32_t row) {
#pragma unroll
        for (int kb = 0; kb < 4; kb++) {
          const uint4 x = ldg_row(lsrc + 32 * kb, row, true);
          v[4 * kb] = x.x; v[4 * kb + 1] = x.y; v[4 * kb + 2] = x.z; v[4 * kb + 3] = x.w;
        }
      };
      auto cvt_row = [&](uint32_t (&v)[16]) {
#pragma unroll
        for (int i = 0; i < 16; i++) v[i] = bf2h(v[i]);
      };
      auto finish = [&](bool one_row) {
        s_chain();
        sched_fence(ck, never);
        epilogue();
        fold();
        uint32_t es = hadd2((c & 1) ? eh1 : eh0, shfl_xor<1>((c & 1) ? eh0 : eh1));
        es = hadd2(es, shfl_xor<2>(es));
        const float w = one_row && (c & 1) ? 0.f : exp_e(es);
        ma = habsmax2(ma, es);
        lsum += w;
        asum = fmaf(w, h_hi(es), asum);
        sched_fence(ck, never);
      };
      ia = gi01.x; ib = gi01.y; ic = gi23.x; id = gi23.y;
      load_row(S0, ia); load_row(S1, ib); load_row(S2, ic); load_row(S3, id);
      if (wg == 0) named_bar_sync(3, 256);
#pragma unroll 1
      for (int r = 0; r < 4; r++) {
        const int e = blockIdx.x * 256 + (2 * r + wg) * 32 + tau;
        load_ix(r + 1);
        lsum = 0.f; asum = 0.f; ma = 0;
        cvt_row(S0); cvt_row(S1);
        products(S0, S0, S1);
        bar_sync2<4, 5>(wg);
        issue();
        cvt_row(S2); cvt_row(S3);
        finish(true);
        products(S0, S1, S2);
        bar_sync2<4, 5>(wg);
        issue();
        load_row(S2, ic);
        finish(false);
        products(S0, S1, S3);
        bar_sync2<4, 5>(wg);
        issue();
        load_row(S0, ia); load_row(S1, ib); load_row(S3, id);
        finish(false);
        lsum += __shfl_xor_sync(0xffffffffu, lsum, 1);
        asum += __shfl_xor_sync(0xffffffffu, asum, 1);
        ma = habsmax2(ma, shfl_xor<1>(ma));
        if ((ma & 0x7fffu) > 0x7000u || ((ma >> 16) & 0x7fffu) >= 0x7c00u) lsum = __int_as_float(0x7fffffff);
        if (c == 0 && e < n_elem)
          asm volatile("st.volatile.global.v2.f32 [%0], {%1,%2};" ::"l"(g_left + e + ck), "f"(lsum), "f"(asum) : "memory");
      }
      if (wg == 0) named_bar_sync(4, 256);
      return;
    }
    sts128p<0>(cv_ptr, convert(g0[0]), v01);
    sts128p<kRow>(cv_ptr, convert(g0[1]), v01);
    sched_fence(ck, never);
    sts128p<2 * kRow>(cv_ptr, convert(g0[2]), v23);
    sts128p<3 * kRow>(cv_ptr, convert(g0[3]), v23);
    TL(9);
    named_bar_sync(wg == 0 ? 3 : 2, wg == 0 ? 256 : 128);
    TL(10);

    static_for<0, 4>([&](auto Kc) {
      constexpr int kb = decltype(Kc)::value;
      const uint4 z = lds128<64 * kb>(ra[5]), x = lds128<64 * kb>(ra[0]), y = lds128<64 * kb>(ra[1]);
      S3[4 * kb] = z.x; S3[4 * kb + 1] = z.y; S3[4 * kb + 2] = z.z; S3[4 * kb + 3] = z.w;
      S0[4 * kb] = x.x; S0[4 * kb + 1] = x.y; S0[4 * kb + 2] = x.z; S0[4 * kb + 3] = x.w;
      S1[4 * kb] = y.x; S1[4 * kb + 1] = y.y; S1[4 * kb + 2] = y.z; S1[4 * kb + 3] = y.w;
      if (kb & 1) sched_fence(ck, never);
    });
#pragma unroll
    for (int i = 0; i < 16; i++) S2[i] = 0;
    static_for<0, AFM_SPLIT1>([&](auto Hc) {
      constexpr int h = decltype(Hc)::value, n = 16 / AFM_SPLIT1;
#pragma unroll
      for (int i = h * n; i < h * n + n; i++) {
        Af[2 * i] = hmul2(S0[i], S3[i]);
        Af[2 * i + 1] = hmul2(S1[i], S3[i]);
        asm volatile("" : "+r"(Af[2 * i]), "+r"(Af[2 * i + 1])::"memory");
      }
      if (h == 0) {
        if (wg == 1) named_bar_sync(5, 256);
        TL(11);
      }
      wgmma_fence();
#pragma unroll
      for (int s = h * n / 2; s < (h * n + n) / 2; s++) {
        const uint64_t d = dB + (uint64_t)(s * (2048 >> 4));
        if (s == 0) wgmma_rs_n128<0>(acc, Af[0], Af[1], Af[2], Af[3], d);
        else wgmma_rs_n128<1>(acc, Af[4 * s], Af[4 * s + 1], Af[4 * s + 2], Af[4 * s + 3], d);
      }
      sched_fence(ck, never);
    });
    wgmma_commit();
    bar_arrive2<5, 4>(wg);
    TL(12);

    auto bump = [&](uint32_t& r) { asm volatile("add.u32 %0, %0, %1;" : "+r"(r) : "n"(2 * kElem)); };
    int left = nb - 1;
    ra[0] += 2 * kElem; ra[1] += 2 * kElem; ra[5] += 2 * kElem;
    uint4 r0, r1;
    uint32_t el = wg, rdy = 0;
    auto tile = [&](auto Tc) {
      constexpr int tt = decltype(Tc)::value;
      TLL(0);
      fold();
      const uint32_t f0 = eh0, f1 = eh1;
      sts32o<(tt == 0 ? 4096 - 2 * ES_STRIDE : (tt - 1) * 1024)>(pt_ptr, eh0);
      sts32o<(tt == 0 ? 4096 - 2 * ES_STRIDE : (tt - 1) * 1024) + 512>(pt_ptr, eh1);
      if (tt == 0) mbar_arrive(sbase + OFF_BAR + 64 + 8 * el);
      if (tt == 3) bar_arrive2p<2, 3, 160>(wg, left == 0);
      if (tt == 2) rdy = mbar_test(sbase + OFF_BAR + 8 * min(el + 2, n_c - 1), 0);
      sched_fence(ck, never);
      if (tt == 0) load_vec(S0, ra[3]);
      if (tt == 1) load_vec(S2, ra[4]);
      if (tt == 2) load_vec(S1, ra[2]);
      if (tt == 3) {
        load_vec(S0, ra[0]);
        r0 = lds128<0>(ra[1]);
        r1 = lds128<64>(ra[1]);
      }
      if (tt == 4) {
        load_vec(S3, ra[5]);
        const uint4 v2 = lds128<128>(ra[1]), v3 = lds128<192>(ra[1]);
        S1[8] = v2.x; S1[9] = v2.y; S1[10] = v2.z; S1[11] = v2.w; S1[12] = v3.x; S1[13] = v3.y; S1[14] = v3.z; S1[15] = v3.w;
        S1[0] = r0.x; S1[1] = r0.y; S1[2] = r0.z; S1[3] = r0.w; S1[4] = r1.x; S1[5] = r1.y; S1[6] = r1.z; S1[7] = r1.w;
      }
      TLL(4);
      s_chain();
      TLL(8);
      TLS();
      epilogue();
      TLL(16);
      if (tt == 2 && !rdy) mbar_wait(sbase + OFF_BAR + 8 * min(el + 2, n_c - 1), 0);
      if (tt == 0) { products(S1, S3, S0); bump(ra[3]); }
      if (tt == 1) { products(S1, S0, S2); bump(ra[4]); }
      if (tt == 2) { products(S0, S2, S1); bump(ra[2]); }
      if (tt == 3) products(S1, S2, S3);
      if (tt == 4) {
        products(S0, S1, S3);
        bump(ra[0]); bump(ra[1]); bump(ra[5]);
        asm volatile("add.u32 %0, %0, %1;" : "+r"(pt_ptr) : "n"(2 * ES_STRIDE));
        el += 2;
      }
      TLL(20);
      keep2(ck, f0, f1, never);
      bar_sync2<4, 5>(wg);
      issue();
    };
#pragma unroll 1
    for (;;) {
      tile(std::integral_constant<int, 0>{});
      tile(std::integral_constant<int, 1>{});
      tile(std::integral_constant<int, 2>{});
      tile(std::integral_constant<int, 3>{});
      if (left == 0) break;
      tile(std::integral_constant<int, 4>{});
      left--;
    }
    TLL(0);
    fold();
    sts32o<3072>(pt_ptr, eh0);
    sts32o<3072 + 512>(pt_ptr, eh1);
    bar_arrive2<10, 11, 160>(wg);
    TH(14);
    s_chain();
    TLL(8);
    TLS();
    epilogue();
    TLL(16);
    TLS();
    fold();
    sts32o<4096>(pt_ptr + ck, eh0);
    sts32o<4096 + 512>(pt_ptr, eh1);
    bar_arrive2<8, 9, 160>(wg);
    TL(13);
    if (wg == 0) {
      named_bar_sync(4, 256);
    } else if (n_c & 1) {
      for (int i = 0; i < 5; i++) {
        named_bar_sync(5, 256);
        named_bar_arrive(4, 256);
      }
    }
  } else {
    {
      asm volatile("setmaxnreg.dec.sync.aligned.u32 104;");
      uint4 wr[16];
#pragma unroll
      for (int r = 0; r < 16; r++) wr[r] = ldg128(W + (32 * wq + 2 * r) * kD + 8 * lane);
      const uint32_t wa = sbase + OFF_B + ((lane >> 3) & 1) * B_NBLK + wq * 4096 + (lane >> 4) * 128;
      const uint32_t lx = (lane & 7) ^ (lane >> 4);
      uint32_t wad[4], mw = 0;
#pragma unroll
      for (int x = 0; x < 4; x++) wad[x] = wa + ((lx ^ (2 * x)) << 4);
      TL(2);
      TL(3);
      static_for<0, 16>([&](auto Rc) {
        constexpr int r = decltype(Rc)::value;
        uint4 v;
        v.x = bf2h_x16(wr[r].x); v.y = bf2h_x16(wr[r].y); v.z = bf2h_x16(wr[r].z); v.w = bf2h_x16(wr[r].w);
        sts128<(r & 3) * 1024 + (r >> 2) * 256>(wad[r >> 2], v);
        mw = babsmax2(babsmax2(mw, wr[r].x), babsmax2(wr[r].y, babsmax2(wr[r].z, wr[r].w)));
        if (r == 3) TL(4);
        if (r == 7 || r == 11) sched_fence(ck, never);
      });
      TL(5);
      fence_proxy_async();
      named_bar_arrive(3, 256);
      TL(6);
      sts32p(sbase + OFF_STAT + wq * 4 + ck, redux_max(absmax_bits(mw)), lane == 0);
    }
    asm volatile("setmaxnreg.dec.sync.aligned.u32 %0;" ::"n"(504 - 2 * AFM_RC));
    if ((int)blockIdx.x >= n_left) helper_rest(idx, table, W, late, base_cnt, extra, last_row, n_left, smem);
    else {
      named_bar_sync(6, 160);
#pragma unroll 1
      for (int q = 2; q < 8; q++) {
        const int e = min((int)blockIdx.x * 256 + q * 32 + (t >> 2), (last_row + 2) / kF - 1);
        const uint32_t row = ldg32(idx + e * kF + ((t & 2) ? ((t & 1) ? 3 : 2) : ((t & 1) ? 1 : 0)));
        asm volatile("prefetch.global.L2 [%0];\nprefetch.global.L2 [%0+128];" ::"l"(table + (size_t)row * kD) : "memory");
      }
    }
  }
}

}

extern "C" void kernel_launch(void* const* d_in, const int* in_sizes, int n_in, void* d_out, int out_size) {
  const int* idx = (const int*)d_in[0];
  const __nv_bfloat16* table = (const __nv_bfloat16*)d_in[1];
  const int* ii = (const int*)d_in[2];
  const int* jj = (const int*)d_in[3];
  const __nv_bfloat16* W = (const __nv_bfloat16*)d_in[4];
  const __nv_bfloat16* bias = (const __nv_bfloat16*)d_in[5];
  const __nv_bfloat16* hvec = (const __nv_bfloat16*)d_in[6];
  const __nv_bfloat16* pvec = (const __nv_bfloat16*)d_in[7];
  __nv_bfloat16* out = (__nv_bfloat16*)d_out;
  const int B = out_size;

  static int num_sms = 0;
  if (num_sms == 0) {
    int dev = 0;
    cudaGetDevice(&dev);
    cudaDeviceGetAttribute(&num_sms, cudaDevAttrMultiProcessorCount, dev);
    cudaFuncSetAttribute(afm_kernel, cudaFuncAttributeMaxDynamicSharedMemorySize, SMEM_BYTES);
  }
  const Sched sched = {{
    0x2d2cb011u, 0x2c9a0662u, 0x2876c228u, 0x26074141u, 0x2655c878u, 0x2985dc43u, 0x18722403u, 0x22299aaeu,
    0x02a6b0b1u, 0x30d73d00u, 0x00941af1u, 0x2ee29c4au, 0x2ad5a410u, 0x21250923u, 0x328a84aeu, 0x0d780599u,
    0x324551f8u, 0x3112a583u, 0x062ca4eeu, 0x155360e3u, 0x1cb204d6u, 0x1f4280c9u, 0x2776e487u, 0x090b60a2u,
    0x2413bf17u, 0x168b28ecu, 0x10c78a70u, 0x2f578ed1u, 0x1a334ac2u, 0x0888c875u, 0x1d5a3249u, 0x2305bf2au
  }};
  for (int off = 0; off < B; off += kMaxChunk) {
    const int n = B - off < kMaxChunk ? B - off : kMaxChunk;
    const int n_left = (n + 255) / 256;
    int n_main = num_sms - n_left;
    if (n_main > n) n_main = n;
    if (n_main < (n + kMaxB - 1) / kMaxB) n_main = (n + kMaxB - 1) / kMaxB;
    const Late late = {{bias, hvec, pvec, pvec}, ii, jj, out + off, sched};
    afm_kernel<<<n_left + n_main, kThreads, SMEM_BYTES>>>(idx + (size_t)off * kF, table, W, n / n_main, n % n_main,
                                                          n * kF - 2, n_left, late);
  }
}
```

```cpp
#include <cuda_runtime.h>
#include <cuda_bf16.h>
#include <cuda_fp16.h>
#include <stdint.h>
#include <type_traits>

namespace {

constexpr int kF = 26;
constexpr int kD = 128;
constexpr int kP = 325;
constexpr int kMaxB = 8;
constexpr int kThreads = 384;
constexpr int kRow = 320;
constexpr int kElem = kF * kRow;

constexpr int B_NBLK = 16 * 1024;
constexpr int OFF_B = 0;
constexpr int OFF_EMB = 2 * B_NBLK;
constexpr int OFF_ES = OFF_EMB + kMaxB * kElem;
constexpr int ES_STRIDE = 5 * 1024;
constexpr int OFF_VEC = OFF_ES + (kMaxB + 2) * ES_STRIDE;
constexpr int OFF_STAT = OFF_VEC + 768;
constexpr int OFF_BAR = OFF_STAT + 128;
constexpr int SMEM_USED = OFF_BAR + 128;
static_assert(OFF_EMB + (kMaxB + 2) * kElem <= SMEM_USED, "unused operand prefetches run up to 2 elements past the end");
constexpr int SMEM_BYTES = SMEM_USED;
static_assert(OFF_ES % 16 == 0 && OFF_VEC % 16 == 0 && OFF_STAT % 16 == 0 && kElem % 128 == 0, "alignment");

struct Sched { uint32_t e[32]; };
struct Late {
  const __nv_bfloat16* vec[4];
  const int* ii;
  const int* jj;
  __nv_bfloat16* out;
  Sched sched;
};

constexpr int kMaxChunk = 8192;
__device__ float2 g_left[kMaxChunk];

__device__ __forceinline__ uint32_t smem_u32(const void* p) { return (uint32_t)__cvta_generic_to_shared(p); }
__device__ __forceinline__ void named_bar_sync(int id, int n) { asm volatile("bar.sync %0, %1;" ::"r"(id), "r"(n) : "memory"); }
__device__ __forceinline__ void named_bar_arrive(int id, int n) { asm volatile("bar.arrive %0, %1;" ::"r"(id), "r"(n) : "memory"); }
template <int A, int B>
__device__ __forceinline__ void bar_sync2(uint32_t sel) {
  asm volatile("{\n.reg .pred p;\nsetp.eq.u32 p, %0, 0;\n@p bar.sync %1, 256;\n@!p bar.sync %2, 256;\n}" ::"r"(sel), "n"(A), "n"(B) : "memory");
}
template <int A, int B, int N = 256>
__device__ __forceinline__ void bar_arrive2(uint32_t sel) {
  asm volatile("{\n.reg .pred p;\nsetp.eq.u32 p, %0, 0;\n@p bar.arrive %1, %3;\n@!p bar.arrive %2, %3;\n}" ::"r"(sel), "n"(A), "n"(B), "n"(N) : "memory");
}
__device__ __forceinline__ void mbar_init(uint32_t bar, uint32_t count) {
  asm volatile("mbarrier.init.shared::cta.b64 [%0], %1;" ::"r"(bar), "r"(count) : "memory");
}
__device__ __forceinline__ void mbar_arrive(uint32_t bar) {
  asm volatile("mbarrier.arrive.shared::cta.b64 _, [%0];" ::"r"(bar) : "memory");
}
__device__ __forceinline__ void mbar_arrive_p(uint32_t bar, bool on) {
  asm volatile("{\n.reg .pred p;\nsetp.ne.u32 p, %1, 0;\n@p mbarrier.arrive.shared::cta.b64 _, [%0];\n}" ::"r"(bar), "r"((uint32_t)on) : "memory");
}
__device__ __forceinline__ uint32_t mbar_test(uint32_t bar, uint32_t parity) {
  uint32_t ok;
  asm volatile("{\n.reg .pred p;\nmbarrier.test_wait.parity.shared::cta.b64 p, [%1], %2;\nselp.u32 %0, 1, 0, p;\n}\n"
               : "=r"(ok) : "r"(bar), "r"(parity) : "memory");
  return ok;
}
__device__ __forceinline__ void mbar_wait(uint32_t bar, uint32_t parity) {
  uint32_t ok, it = 0;
  do {
    asm volatile("{\n.reg .pred p;\nmbarrier.try_wait.parity.shared::cta.b64 p, [%1], %2, %3;\nselp.u32 %0, 1, 0, p;\n}\n"
                 : "=r"(ok) : "r"(bar), "r"(parity), "r"(20000) : "memory");
  } while (!ok && ++it < (1u << 16));
}
__device__ __forceinline__ void wgmma_fence() { asm volatile("wgmma.fence.sync.aligned;" ::: "memory"); }
__device__ __forceinline__ void wgmma_commit() { asm volatile("wgmma.commit_group.sync.aligned;" ::: "memory"); }
template <int N>
__device__ __forceinline__ void wgmma_wait() { asm volatile("wgmma.wait_group.sync.aligned %0;" ::"n"(N) : "memory"); }
__device__ __forceinline__ void fence_proxy_async() { asm volatile("fence.proxy.async.shared::cta;" ::: "memory"); }

__device__ __forceinline__ uint32_t hmul2(uint32_t a, uint32_t b) {
  uint32_t d;
  asm("mul.rn.f16x2 %0, %1, %2;" : "=r"(d) : "r"(a), "r"(b));
  return d;
}
__device__ __forceinline__ uint32_t hadd2(uint32_t a, uint32_t b) {
  uint32_t d;
  asm("add.rn.f16x2 %0, %1, %2;" : "=r"(d) : "r"(a), "r"(b));
  return d;
}
__device__ __forceinline__ uint32_t hfma2(uint32_t a, uint32_t b, uint32_t c) {
  uint32_t d;
  asm("fma.rn.f16x2 %0, %1, %2, %3;" : "=r"(d) : "r"(a), "r"(b), "r"(c));
  return d;
}
__device__ __forceinline__ uint32_t bias_relu2(uint32_t x, uint32_t nb) {
  uint32_t d;
  asm("max.NaN.f16x2 %0, %1, %2;" : "=r"(d) : "r"(x), "r"(nb));
  return d;
}
__device__ __forceinline__ uint32_t habsmax2(uint32_t a, uint32_t b) {
  uint32_t d;
  asm("max.NaN.xorsign.abs.f16x2 %0, %1, %2;" : "=r"(d) : "r"(a), "r"(b));
  return d;
}
__device__ __forceinline__ uint32_t babsmax2(uint32_t a, uint32_t b) {
  uint32_t d;
  asm("max.NaN.xorsign.abs.bf16x2 %0, %1, %2;" : "=r"(d) : "r"(a), "r"(b));
  return d;
}
__device__ __forceinline__ uint32_t bf2h(uint32_t x) {
  uint32_t d;
  asm("cvt.rn.f16x2.f32 %0, %1, %2;" : "=r"(d) : "f"(__uint_as_float(x & 0xffff0000u)), "f"(__uint_as_float(x << 16)));
  return d;
}
__device__ __forceinline__ uint32_t bf2h_x16(uint32_t x) {
  uint32_t hi, lo, d;
  asm("fma.rn.bf16x2 %0, %1, %2, %3;" : "=r"(hi) : "r"(x), "r"(0x41800000u), "r"(0u));
  asm("{\n.reg .b16 l, h;\n.reg .b32 t;\nmov.b32 {l, h}, %1;\nmov.b32 t, {l, l};\nfma.rn.bf16x2 %0, t, %2, %3;\n}"
      : "=r"(lo) : "r"(x), "r"(0x41800000u), "r"(0u));
  asm("cvt.rn.f16x2.f32 %0, %1, %2;" : "=r"(d) : "f"(__uint_as_float(hi)), "f"(__uint_as_float(lo)));
  return d;
}
template <bool HI_FMA>
__device__ __forceinline__ uint32_t bf2h_f(uint32_t x) {
  uint32_t hi = x & 0xffff0000u, lo, d;
  if (HI_FMA) asm("fma.rn.bf16x2 %0, %1, %2, %3;" : "=r"(hi) : "r"(x), "r"(0x3f800000u), "r"(0u));
  asm("{\n.reg .b16 l, h;\n.reg .b32 t;\nmov.b32 {l, h}, %1;\nmov.b32 t, {l, l};\nfma.rn.bf16x2 %0, t, %2, %3;\n}"
      : "=r"(lo) : "r"(x), "r"(0x3f800000u), "r"(0u));
  asm("cvt.rn.f16x2.f32 %0, %1, %2;" : "=r"(d) : "f"(__uint_as_float(hi)), "f"(__uint_as_float(lo)));
  return d;
}
__device__ __forceinline__ uint4 convert(uint4 v) { return make_uint4(bf2h(v.x), bf2h(v.y), bf2h(v.z), bf2h(v.w)); }
__device__ __forceinline__ uint4 convert_f(uint4 v) {
  return make_uint4(bf2h_f<false>(v.x), bf2h_f<true>(v.y), bf2h_f<false>(v.z), bf2h_f<true>(v.w));
}
__device__ __forceinline__ float h_lo(uint32_t x) { return __half2float(__ushort_as_half((unsigned short)(x & 0xffffu))); }
__device__ __forceinline__ float h_hi(uint32_t x) { return __half2float(__ushort_as_half((unsigned short)(x >> 16))); }
__device__ __forceinline__ uint32_t redux_max(uint32_t v) {
  uint32_t d;
  asm volatile("redux.sync.max.u32 %0, %1, 0xffffffff;" : "=r"(d) : "r"(v));
  return d;
}
__device__ __forceinline__ uint32_t absmax_bits(uint32_t m) { return max(m & 0x7fffu, (m >> 16) & 0x7fffu); }

template <int OFF>
__device__ __forceinline__ uint4 lds128(uint32_t addr) {
  uint4 v;
  asm volatile("ld.shared.v4.u32 {%0,%1,%2,%3}, [%4+%5];" : "=r"(v.x), "=r"(v.y), "=r"(v.z), "=r"(v.w) : "r"(addr), "n"(OFF));
  return v;
}
template <int OFF>
__device__ __forceinline__ void sts128(uint32_t addr, uint4 v) {
  asm volatile("st.shared.v4.u32 [%0+%5], {%1,%2,%3,%4};" ::"r"(addr), "r"(v.x), "r"(v.y), "r"(v.z), "r"(v.w), "n"(OFF) : "memory");
}
__device__ __forceinline__ uint32_t lds32(uint32_t addr) {
  uint32_t v;
  asm volatile("ld.shared.u32 %0, [%1];" : "=r"(v) : "r"(addr));
  return v;
}
__device__ __forceinline__ void sts32(uint32_t addr, uint32_t v) { asm volatile("st.shared.u32 [%0], %1;" ::"r"(addr), "r"(v) : "memory"); }
__device__ __forceinline__ uint32_t ldg32(const void* p) {
  uint32_t v;
  asm volatile("ld.global.u32 %0, [%1];" : "=r"(v) : "l"(p) : "memory");
  return v;
}
__device__ __forceinline__ uint4 ldg128(const void* p) {
  uint4 v;
  asm volatile("ld.global.v4.u32 {%0,%1,%2,%3}, [%4];" : "=r"(v.x), "=r"(v.y), "=r"(v.z), "=r"(v.w) : "l"(p) : "memory");
  return v;
}
__device__ __forceinline__ uint2 ldg64(const void* p) {
  uint2 v;
  asm volatile("ld.global.v2.u32 {%0,%1}, [%2];" : "=r"(v.x), "=r"(v.y) : "l"(p) : "memory");
  return v;
}
__device__ __forceinline__ uint2 ldg64p(const void* p, bool on) {
  uint2 v;
  asm volatile("{\n.reg .pred p;\nsetp.ne.u32 p, %3, 0;\n@p ld.volatile.global.v2.u32 {%0,%1}, [%2];\n}" : "=r"(v.x), "=r"(v.y) : "l"(p), "r"((uint32_t)on) : "memory");
  return v;
}
__device__ __forceinline__ uint4 ldg_row(const void* base, uint32_t row, bool on) {
  uint4 v;
  asm volatile("{\n.reg .pred p;\n.reg .b64 a;\nsetp.ne.u32 p, %6, 0;\nmad.wide.u32 a, %5, 256, %4;\n@p ld.global.v4.u32 {%0,%1,%2,%3}, [a];\n}"
               : "=r"(v.x), "=r"(v.y), "=r"(v.z), "=r"(v.w) : "l"(base), "r"(row), "r"((uint32_t)on) : "memory");
  return v;
}
template <int OFF>
__device__ __forceinline__ void sts128p(uint32_t addr, uint4 v, bool on) {
  asm volatile("{\n.reg .pred p;\nsetp.ne.u32 p, %6, 0;\n@p st.shared.v4.u32 [%0+%5], {%1,%2,%3,%4};\n}"
               ::"r"(addr), "r"(v.x), "r"(v.y), "r"(v.z), "r"(v.w), "n"(OFF), "r"((uint32_t)on) : "memory");
}
__device__ __forceinline__ void sts32p(uint32_t addr, uint32_t v, bool on) {
  asm volatile("{\n.reg .pred p;\nsetp.ne.u32 p, %2, 0;\n@p st.shared.u32 [%0], %1;\n}" ::"r"(addr), "r"(v), "r"((uint32_t)on) : "memory");
}
__device__ __forceinline__ uint32_t shfl_xor_v(uint32_t v, int m) {
  uint32_t d;
  asm volatile("shfl.sync.bfly.b32 %0, %1, %2, 0x1f, 0xffffffff;" : "=r"(d) : "r"(v), "r"(m));
  return d;
}
template <int M>
__device__ __forceinline__ uint32_t shfl_xor(uint32_t v) {
  uint32_t d;
  asm volatile("shfl.sync.bfly.b32 %0, %1, %2, 0x1f, 0xffffffff;" : "=r"(d) : "r"(v), "n"(M));
  return d;
}
template <int I, int N, typename F>
__device__ __forceinline__ void static_for(F&& f) {
  if constexpr (I < N) {
    f(std::integral_constant<int, I>{});
    static_for<I + 1, N>(f);
  }
}
template <int N>
__device__ __forceinline__ void fence_regs(uint32_t (&r)[N]) {
#pragma unroll
  for (int i = 0; i < N; i++) asm volatile("" : "+r"(r[i])::"memory");
}
__device__ __forceinline__ void load_vec(uint32_t (&v)[16], uint32_t a) {
  const uint4 v0 = lds128<0>(a), v1 = lds128<64>(a), v2 = lds128<128>(a), v3 = lds128<192>(a);
  v[0] = v0.x; v[1] = v0.y; v[2] = v0.z; v[3] = v0.w; v[4] = v1.x; v[5] = v1.y; v[6] = v1.z; v[7] = v1.w;
  v[8] = v2.x; v[9] = v2.y; v[10] = v2.z; v[11] = v2.w; v[12] = v3.x; v[13] = v3.y; v[14] = v3.z; v[15] = v3.w;
}

template <int OFF>
__device__ __forceinline__ void sts32o(uint32_t addr, uint32_t v) {
  asm volatile("st.shared.u32 [%0+%2], %1;" ::"r"(addr), "r"(v), "n"(OFF) : "memory");
}
__device__ __forceinline__ void keep2(uint32_t& ck, uint32_t a, uint32_t b, uint32_t never) {
  asm volatile("{\n.reg .pred p;\nsetp.ne.u32 p, %3, 0;\n@p xor.b32 %0, %1, %2;\n}" : "+r"(ck) : "r"(a), "r"(b), "r"(never));
}
__device__ __forceinline__ float exp_e(uint32_t es) {
  float w;
  asm("ex2.approx.ftz.f32 %0, %1;" : "=f"(w) : "f"(h_lo(es) * (1.4426950408889634f / 256.f)));
  return w;
}
__device__ __forceinline__ uint32_t clock32() {
  uint32_t v;
  asm volatile("mov.u32 %0, %%clock;" : "=r"(v)::"memory");
  return v;
}
__device__ __forceinline__ void sched_fence(uint32_t& ck, uint32_t never) {
  asm volatile("{\n.reg .pred p;\nsetp.ne.u32 p, %1, 0;\n@p mov.u32 %0, %%clock;\n}" : "+r"(ck) : "r"(never) : "memory");
}

template <int ACCUM>
__device__ __forceinline__ void wgmma_rs_n128(uint32_t (&d)[32], uint32_t a0, uint32_t a1, uint32_t a2, uint32_t a3, uint64_t descB) {
  if (ACCUM == 1) {
    asm volatile(
        "wgmma.mma_async.sync.aligned.m64n128k16.f16.f16.f16 "
        "{%0, %1, %2, %3, %4, %5, %6, %7, %8, %9, %10, %11, %12, %13, %14, %15, %16, %17, %18, %19, %20, %21, %22, %23, %24, %25, %26, %27, %28, %29, %30, %31}, "
        "{%32, %33, %34, %35}, %36, 1, 1, 1, 1;\n"
        : "+r"(d[0]), "+r"(d[1]), "+r"(d[2]), "+r"(d[3]), "+r"(d[4]), "+r"(d[5]), "+r"(d[6]), "+r"(d[7]), "+r"(d[8]), "+r"(d[9]), "+r"(d[10]), "+r"(d[11]), "+r"(d[12]), "+r"(d[13]), "+r"(d[14]), "+r"(d[15]), "+r"(d[16]), "+r"(d[17]), "+r"(d[18]), "+r"(d[19]), "+r"(d[20]), "+r"(d[21]), "+r"(d[22]), "+r"(d[23]), "+r"(d[24]), "+r"(d[25]), "+r"(d[26]), "+r"(d[27]), "+r"(d[28]), "+r"(d[29]), "+r"(d[30]), "+r"(d[31])
        : "r"(a0), "r"(a1), "r"(a2), "r"(a3), "l"(descB));
  }
  if (ACCUM == 0) {
    asm volatile(
        "wgmma.mma_async.sync.aligned.m64n128k16.f16.f16.f16 "
        "{%0, %1, %2, %3, %4, %5, %6, %7, %8, %9, %10, %11, %12, %13, %14, %15, %16, %17, %18, %19, %20, %21, %22, %23, %24, %25, %26, %27, %28, %29, %30, %31}, "
        "{%32, %33, %34, %35}, %36, 0, 1, 1, 1;\n"
        : "=r"(d[0]), "=r"(d[1]), "=r"(d[2]), "=r"(d[3]), "=r"(d[4]), "=r"(d[5]), "=r"(d[6]), "=r"(d[7]), "=r"(d[8]), "=r"(d[9]), "=r"(d[10]), "=r"(d[11]), "=r"(d[12]), "=r"(d[13]), "=r"(d[14]), "=r"(d[15]), "=r"(d[16]), "=r"(d[17]), "=r"(d[18]), "=r"(d[19]), "=r"(d[20]), "=r"(d[21]), "=r"(d[22]), "=r"(d[23]), "=r"(d[24]), "=r"(d[25]), "=r"(d[26]), "=r"(d[27]), "=r"(d[28]), "=r"(d[29]), "=r"(d[30]), "=r"(d[31])
        : "r"(a0), "r"(a1), "r"(a2), "r"(a3), "l"(descB));
  }
}

__device__ __forceinline__ float rbf(float x) { return __bfloat162float(__float2bfloat16_rn(x)); }
__device__ __forceinline__ float warp_sum(float v) {
#pragma unroll
  for (int o = 16; o > 0; o >>= 1) v += __shfl_xor_sync(0xffffffffu, v, o);
  return v;
}

__device__ __noinline__ void general_element(const int* __restrict__ idx, const __nv_bfloat16* __restrict__ table,
                                             const int* __restrict__ ii, const int* __restrict__ jj,
                                             const __nv_bfloat16* __restrict__ W, const __nv_bfloat16* __restrict__ bias,
                                             const __nv_bfloat16* __restrict__ hvec, const __nv_bfloat16* __restrict__ pvec,
                                             __nv_bfloat16* __restrict__ out, float* ev) {
  const int lane = threadIdx.x & 31;
  auto pair4 = [&](int p, float (&pr)[4]) {
    const __nv_bfloat16* a = table + (size_t)idx[ii[p]] * kD + 4 * lane;
    const __nv_bfloat16* b = table + (size_t)idx[jj[p]] * kD + 4 * lane;
#pragma unroll
    for (int q = 0; q < 4; q++) pr[q] = rbf(__bfloat162float(a[q]) * __bfloat162float(b[q]));
  };
  float m = -INFINITY;
  bool has_nan = false;
  for (int p = 0; p < kP; p++) {
    float pr[4], x[4] = {0.f, 0.f, 0.f, 0.f};
    pair4(p, pr);
    for (int l = 0; l < 32; l++) {
#pragma unroll
      for (int q = 0; q < 4; q++) {
        const float v = __shfl_sync(0xffffffffu, pr[q], l);
        const uint2 w = *reinterpret_cast<const uint2*>(W + (4 * l + q) * kD + 4 * lane);
        x[0] = fmaf(v, __uint_as_float(w.x << 16), x[0]);
        x[1] = fmaf(v, __uint_as_float(w.x & 0xffff0000u), x[1]);
        x[2] = fmaf(v, __uint_as_float(w.y << 16), x[2]);
        x[3] = fmaf(v, __uint_as_float(w.y & 0xffff0000u), x[3]);
      }
    }
    float e = 0.f;
#pragma unroll
    for (int q = 0; q < 4; q++) {
      const float y = rbf(rbf(x[q]) + __bfloat162float(bias[4 * lane + q]));
      e = fmaf(rbf(0.5f * rbf(y + fabsf(y))), __bfloat162float(hvec[4 * lane + q]), e);
    }
    e = rbf(warp_sum(e));
    has_nan |= (e != e);
    m = fmaxf(m, e);
    if (lane == 0) ev[p] = e;
  }
  __syncwarp();
  float l = 0.f;
  for (int p = lane; p < kP; p += 32) l += expf(ev[p] - m);
  l = warp_sum(l);
  float pooled[4] = {0.f, 0.f, 0.f, 0.f};
  for (int p = 0; p < kP; p++) {
    float pr[4];
    pair4(p, pr);
    const float al = rbf(expf(ev[p] - m) / l);
#pragma unroll
    for (int q = 0; q < 4; q++) pooled[q] = fmaf(al, pr[q], pooled[q]);
  }
  float o = 0.f;
#pragma unroll
  for (int q = 0; q < 4; q++) o = fmaf(rbf(pooled[q]), __bfloat162float(pvec[4 * lane + q]), o);
  o = warp_sum(o);
  if (has_nan) o = __int_as_float(0x7fffffff);
  if (lane == 0) *out = __float2bfloat16_rn(o);
}

__device__ __forceinline__ void helper_rest(const int* __restrict__ idx, const __nv_bfloat16* __restrict__ table,
                                            const __nv_bfloat16* __restrict__ W, const Late& late, int base_cnt, int extra,
                                            int last_row, int n_left, uint8_t* smem) {
  constexpr uint32_t sbase = 0x400u;
  uint32_t tid, cta;
  asm volatile("mov.u32 %0, %%tid.x;\nmov.u32 %1, %%ctaid.x;" : "=r"(tid), "=r"(cta));
  const int t = tid & 127, lane = tid & 31, wq = (tid >> 5) & 3;
  cta -= n_left;
  const int n_out = base_cnt + ((int)cta < extra ? 1 : 0), n_c = max(n_out, 2);
  const int b0 = cta * base_cnt + min((int)cta, extra);
  const int grp = 7 - (t >> 4);
  const bool v01 = grp < 7, v23 = grp < 6;
  int irow = (b0 + (n_c > 2 ? 2 : 0)) * kF + 4 * grp;
  uint2 gi01 = ldg64(idx + min(irow, last_row));
  uint2 gi23 = ldg64(idx + min(irow + 2, last_row));
  const __nv_bfloat16* gsrc = table + (t & 15) * 8;
  uint32_t cv_ptr = sbase + OFF_EMB + 2 * kElem + 4 * grp * kRow + (t & 15) * 16;
  uint32_t me = 0, ck = 0;
  auto track = [&](const uint4& a, const uint4& b, bool on) {
    const uint32_t m = babsmax2(babsmax2(babsmax2(a.x, a.y), babsmax2(a.z, a.w)), babsmax2(babsmax2(b.x, b.y), babsmax2(b.z, b.w)));
    me = babsmax2(me, on ? m : 0u);
  };
  named_bar_sync(6, 160);
#pragma unroll 1
  for (int e = 2; e < n_c + 2; e++) {
    const uint4 g0 = ldg_row(gsrc, gi01.x, v01), g1 = ldg_row(gsrc, gi01.y, v01);
    const uint4 g2 = ldg_row(gsrc, gi23.x, v23), g3 = ldg_row(gsrc, gi23.y, v23);
    irow += e + 1 == n_c ? (1 - n_c) * kF : kF;
    gi01 = ldg64(idx + min(irow, last_row));
    gi23 = ldg64(idx + min(irow + 2, last_row));
    uint4 h0 = convert(g0), h1 = convert(g1), h2 = convert(g2), h3 = convert(g3);
    asm volatile("" : "+r"(h0.x), "+r"(h0.y), "+r"(h0.z), "+r"(h0.w), "+r"(h1.x), "+r"(h1.y), "+r"(h1.z), "+r"(h1.w),
                      "+r"(h2.x), "+r"(h2.y), "+r"(h2.z), "+r"(h2.w), "+r"(h3.x), "+r"(h3.y), "+r"(h3.z), "+r"(h3.w));
    sched_fence(ck, tid >> 10);
    sts128p<0>(cv_ptr, h0, v01 && e < n_c);
    sts128p<kRow>(cv_ptr, h1, v01 && e < n_c);
    sts128p<2 * kRow>(cv_ptr, h2, v23 && e < n_c);
    sts128p<3 * kRow>(cv_ptr, h3, v23 && e < n_c);
    __syncwarp();
    mbar_arrive_p(sbase + OFF_BAR + 8 * e, lane == 0 && e < n_c);
    sched_fence(ck, tid >> 10);
    cv_ptr += kElem;
    track(g0, g1, v01);
    track(g2, g3, v23);
  }
  bool ok_cta;
  float ds;
  {
    const uint32_t s0 = ldg32(late.vec[t >> 6] + 2 * (t & 63)), s1 = ldg32(late.vec[2] + 2 * (t & 63));
    const uint32_t s2 = ldg32(late.vec[(t >> 6) ^ 1] + 2 * (t & 63));
    uint32_t pi[3], pj[3];
#pragma unroll
    for (int r = 0; r < 3; r++) {
      pi[r] = ldg32(late.ii + min(t + 128 * r, kP - 1));
      pj[r] = ldg32(late.jj + min(t + 128 * r, kP - 1));
    }
    float v0 = 16.f * (fabsf(__uint_as_float(s0 << 16)) + fabsf(__uint_as_float(s0 & 0xffff0000u)));
    float v1 = 16.f * (fabsf(__uint_as_float(s1 << 16)) + fabsf(__uint_as_float(s1 & 0xffff0000u)));
    if (t >= 64) v1 = fabsf(__uint_as_float(s0 << 16) * __uint_as_float(s2 << 16)) +
                      fabsf(__uint_as_float(s0 & 0xffff0000u) * __uint_as_float(s2 & 0xffff0000u));
    bool good = true;
#pragma unroll
    for (int r = 0; r < 3; r++)
      good &= (pi[r] < pj[r]) & (pj[r] < kF) & (((pi[r] * (2 * kF - 1 - pi[r])) >> 1) + pj[r] - pi[r] - 1 == min(t + 128 * r, kP - 1));
    if (!good) v0 = __int_as_float(0x7fffffff);
    v0 = warp_sum(v0);
    v1 = warp_sum(v1);
    sts32p(sbase + OFF_STAT + 64 + wq * 4, __float_as_uint(v0), lane == 0);
    sts32p(sbase + OFF_STAT + 80 + wq * 4, __float_as_uint(v1), lane == 0);
    sts32p(sbase + OFF_STAT + 16 + wq * 4 + ck, redux_max(absmax_bits(me)), lane == 0);
    named_bar_sync(6, 128);
    const uint32_t st = lds32(sbase + OFF_STAT + lane * 4);
    const float Wm = 2048.f * __uint_as_float(redux_max(lane < 4 ? st : 0u) << 16);
    const float M = __uint_as_float(redux_max(lane >= 4 && lane < 8 ? st : 0u) << 16);
    const float sp = __uint_as_float(st) + __shfl_xor_sync(0xffffffffu, __uint_as_float(st), 1);
    const float Bs = __shfl_sync(0xffffffffu, sp, 16);
    const float Hs = __shfl_sync(0xffffffffu, sp, 18);
    const float Ps = __shfl_sync(0xffffffffu, sp, 20);
    const float HB = __shfl_sync(0xffffffffu, sp, 22);
    const float M2 = M * M, X = fmaf(M2, Wm, Bs), G = fmaf(2.f, M, 1.f);
    constexpr float u = 1.f / 33554432.f;
    const float de = u * (Hs * (Wm * G + 128.f * M2 + 16.f) + 128.f * X + 256.f);
    ds = u * (Ps * G + 128.f * M2 + 256.f);
    ok_cta = M2 <= 60000.f && Wm <= 128.f * 60000.f && X <= 60000.f && Hs <= 60000.f && Ps <= 60000.f && de <= 1.f && HB <= 64.f;
  }
#pragma unroll 1
  for (int e = wq; e < n_c; e += 4) {
    const uint32_t ea = sbase + OFF_ES + (2 + e) * ES_STRIDE + lane * 16;
    float l = 0.f, a = 0.f;
    if (lane == 0 && e < n_out) {
      float2* const gp = g_left + b0 + e;
      for (uint32_t it = 0; it < (1u << 22); it++) {
        asm volatile("{\n.reg .b64 v;\nld.volatile.global.b64 v, [%2];\nmov.b64 {%0,%1}, v;\n}" : "=f"(l), "=f"(a) : "l"(gp) : "memory");
        if (__float_as_uint(l) != 0u) break;
        __nanosleep(200);
      }
      asm volatile("st.volatile.global.b64 [%0], %1;" ::"l"(gp), "l"(0ull) : "memory");
    }
    __syncwarp();
    uint32_t mx = lane == 0 && !(l > 0.f) ? 0x7fffu : 0u;
    auto take = [&](const uint4& v) {
      const uint32_t es = hadd2(hadd2(v.x, v.y), hadd2(v.z, v.w));
      const float w = exp_e(es);
      mx = habsmax2(mx, es);
      l += w;
      a = fmaf(w, h_hi(es), a);
    };
    const bool last = e + 2 >= n_c;
    if (last) named_bar_sync(13 + (e & 1), 160);
    else mbar_wait(sbase + OFF_BAR + 80 + 8 * e, 0);
    {
      uint4 v[6];
      static_for<0, 6>([&](auto Qc) { v[decltype(Qc)::value] = lds128<decltype(Qc)::value * 512>(ea); });
      sched_fence(ck, tid >> 10);
#pragma unroll
      for (int q = 0; q < 6; q++) take(v[q]);
    }
    __nv_bfloat16* op = late.out + b0 + e;
    asm volatile("" : "+l"(op));
    if (last) named_bar_sync(10 + (e & 1), 160);
    take(lds128<3072>(ea));
    take(lds128<3072 + 512>(ea));
    asm volatile("" : "+f"(l), "+f"(a), "+r"(mx));
    sched_fence(ck, tid >> 10);
    asm volatile("{\n.reg .pred p, q;\nsetp.ne.u32 q, %1, 0;\nsetp.eq.and.u32 p|q, %0, 0, q;\n@p bar.sync 8, 160;\n@q bar.sync 9, 160;\n}"
                 ::"r"(e & 1), "r"((uint32_t)last) : "memory");
    {
      const uint4 v0 = lds128<4096>(ea + ck), v1 = lds128<4096 + 512>(ea);
      take(v0);
      take(v1);
    }
    const uint32_t big = __ballot_sync(0xffffffffu, ds <= fabsf(h_hi(mx)) * (1.f / 16384.f));
    const uint32_t bad = __ballot_sync(0xffffffffu, ((mx & 0x7fffu) > 0x7000u) | ((mx & 0x7c000000u) == 0x7c000000u));
    const bool ok = (big != 0u) & (bad == 0u) & ok_cta;
#pragma unroll
    for (int o = 0; o < 5; o++) {
      l += __uint_as_float(shfl_xor_v(__float_as_uint(l), 1 << o));
      a += __uint_as_float(shfl_xor_v(__float_as_uint(a), 1 << o));
    }
    float r;
    asm("rcp.approx.ftz.f32 %0, %1;" : "=f"(r) : "f"(l));
    if (lane == 0 && e < n_out) *op = __float2bfloat16_rn(a * 0.0625f * r);
    if (!ok && e < n_out)
      general_element(idx + (b0 + e) * kF, table, late.ii, late.jj, W, late.vec[0], late.vec[1], late.vec[2], op, reinterpret_cast<float*>(smem + OFF_EMB + e * kElem));
  }
}

__global__ void __launch_bounds__(kThreads, 1)
afm_kernel(const int* __restrict__ idx, const __nv_bfloat16* __restrict__ table, const __nv_bfloat16* __restrict__ W,
           int base_cnt, int extra, int last_row, int n_left, const __grid_constant__ Late late) {
  extern __shared__ __align__(1024) uint8_t smem[];
  constexpr uint32_t sbase = 0x400u;

  const int tid = threadIdx.x;
  const int t = tid & 127;
  const int lane = tid & 31;
  const int warp = tid >> 5;
  uint32_t ck = 0;
  uint32_t never = tid >> 10;
  const int cta = max((int)blockIdx.x - n_left, 0);
  const int b0 = cta * base_cnt + min(cta, extra);
  const int grp = 7 - (t >> 4);
  const bool v01 = grp < 7, v23 = grp < 6;
  const bool is_left = (int)blockIdx.x < n_left;
  const int irow = (b0 + (tid >> 7)) * kF + 4 * grp;
  uint2 gi01 = ldg64p(idx + min(irow, last_row), tid < 256);
  uint2 gi23 = ldg64p(idx + min(irow + 2, last_row), tid < 256);
  asm volatile("{\n.reg .pred p;\nsetp.ge.u32 p, %1, %2;\n@p prefetch.global.L2 [%0];\n}" ::"l"(W + ((blockIdx.x * 32 + tid) & 255) * 64), "r"(tid), "n"(384 - 32) : "memory");
  sched_fence(ck, never);
  const int wq = warp & 3;
  const int wg = __shfl_sync(0xffffffffu, tid >> 7, 0);
  const int n_out = base_cnt + (cta < extra ? 1 : 0);
  const int n_c = max(n_out, 2);
  const __nv_bfloat16* gsrc = table + (t & 15) * 8;
  asm volatile("" : "+l"(gsrc));
  uint32_t cv_ptr = sbase + OFF_EMB + wg * kElem + 4 * grp * kRow + (t & 15) * 16;

  if (wg < 2) {
    const int c = lane & 3;
    const int tau = t >> 2;
    if (wg == 0) {
      asm volatile("cp.async.ca.shared.global [%0], [%1], 4;\ncp.async.ca.shared.global [%0+4], [%2], 4;\ncp.async.commit_group;"
                   ::"r"(sbase + OFF_ES + t * 8), "l"(late.vec[t >> 6] + 2 * (t & 63)), "l"(late.vec[2] + 2 * (t & 63)) : "memory");
    }
    const int nb = (n_c - wg + 1) >> 1;
    const uint32_t sc = late.sched.e[tau];
    uint4 g0[4];
    const bool q01 = v01 && !is_left, q23 = v23 && !is_left;
    sched_fence(ck, never);
    if (wg == 1) {
      uint32_t y;
      asm volatile("or.b32 %0, %1, %2;" : "=r"(y) : "r"(gi01.x), "r"(gi23.x));
      const uint32_t t0 = clock32() + (y >> 31);
      while (clock32() - t0 < 450) {
      }
    }
    sched_fence(ck, never);
    g0[0] = ldg_row(gsrc, gi01.x, q01);
    g0[1] = ldg_row(gsrc, gi01.y, q01);
    g0[2] = ldg_row(gsrc, gi23.x, q23);
    g0[3] = ldg_row(gsrc, gi23.y, q23);
    sched_fence(ck, never);
    const int* lip = idx + min((int)(blockIdx.x * 256 + tau * 8 + wg) * kF, last_row + 2 - kF);
    const uint2 li01 = ldg64p(lip, is_left), li23 = ldg64p(lip + 2, is_left);
    if (warp == 0) {
      if (lane == 0) {
#pragma unroll
        for (int i = 0; i < 16; i++) mbar_init(sbase + OFF_BAR + 8 * i, i < 2 ? 1 : i < 8 ? 4 : 128);
        mbar_arrive(sbase + OFF_BAR);
        mbar_arrive(sbase + OFF_BAR + 8);
      }
      if (smem_u32(smem) != sbase) __trap();
      __syncwarp();
      named_bar_arrive(6, 160);
    }
    if (wg == 0) {
      asm volatile("cp.async.wait_group 0;" ::: "memory");
      const uint32_t s0 = lds32(sbase + OFF_ES + t * 8), s1 = lds32(sbase + OFF_ES + t * 8 + 4);
      sts32(sbase + OFF_VEC + ((t & 112u) | ((t & 3u) << 2) | ((t >> 2) & 3u)) * 4,
            bf2h_x16(s0) ^ (t < 64 ? 0x80008000u : 0u));
      sts32(sbase + OFF_VEC + 512 + (t & 63) * 4, bf2h_x16(s1));
      named_bar_arrive(12, 256);
    }
    asm volatile("{\n.reg .pred p;\nsetp.eq.u32 p, %0, 0;\n@p bar.sync 1, 128;\n@!p bar.sync 12, 256;\n}" ::"r"(wg) : "memory");
    sched_fence(ck, never);
    uint32_t bs[16], hs[16], ps[16];
    load_vec(ps, sbase + OFF_VEC + 512 + c * 16);
    load_vec(bs, sbase + OFF_VEC + c * 16);
    load_vec(hs, sbase + OFF_VEC + 256 + c * 16);
    sched_fence(ck, never);
    if (wg == 1) named_bar_sync(7, 256);
    asm volatile("setmaxnreg.inc.sync.aligned.u32 %0;" ::"n"(216));
    if (wg == 0) named_bar_arrive(7, 256);
    uint32_t pt_ptr = shfl_xor<0>(sbase + OFF_ES + (2 + wg) * ES_STRIDE + t * 4);
    never = pt_ptr >> 31;
    uint32_t ra[6];
#pragma unroll
    for (int r = 0; r < 6; r++) ra[r] = sbase + OFF_EMB + wg * kElem + c * 16 + ((sc >> (5 * r)) & 31u) * kRow;
    asm volatile("" : "+r"(ra[0]), "+r"(ra[1]), "+r"(ra[2]), "+r"(ra[3]), "+r"(ra[4]), "+r"(ra[5]));
    sched_fence(ck, never);
    uint32_t Af[32], acc[32], S0[16], S1[16], S2[16], S3[16];
    constexpr uint64_t dB = (uint64_t)(((sbase + OFF_B) & 0x3FFFFu) >> 4) | ((uint64_t)(B_NBLK >> 4) << 16) |
                            ((uint64_t)(1024 >> 4) << 32) | ((uint64_t)1 << 62);
    auto products = [&](const uint32_t (&X)[16], const uint32_t (&Y)[16], const uint32_t (&Z)[16]) {
#pragma unroll
      for (int i = 0; i < 16; i++) {
        Af[2 * i] = hmul2(X[i], Z[i]);
        Af[2 * i + 1] = hmul2(Y[i], Z[i]);
      }
    };
    auto mma_tile = [&]() {
      fence_regs(Af);
      wgmma_fence();
#pragma unroll
      for (int s = 0; s < 8; s++) {
        const uint64_t d = dB + (uint64_t)(s * (2048 >> 4));
        if (s == 0) wgmma_rs_n128<0>(acc, Af[0], Af[1], Af[2], Af[3], d);
        else wgmma_rs_n128<1>(acc, Af[4 * s], Af[4 * s + 1], Af[4 * s + 2], Af[4 * s + 3], d);
      }
      wgmma_commit();
    };
    auto issue = [&]() {
      mma_tile();
      bar_arrive2<5, 4>(wg);
    };
    uint32_t eh0 = 0, eh1 = 0, sh0 = 0, sh1 = 0;
    auto fold = [&]() {
      eh0 = hadd2(__byte_perm(eh0, sh0, 0x5410), __byte_perm(eh0, sh0, 0x7632));
      eh1 = hadd2(__byte_perm(eh1, sh1, 0x5410), __byte_perm(eh1, sh1, 0x7632));
    };
    auto s_chain = [&]() {
      sh0 = hmul2(Af[0], ps[0]);
      sh1 = hmul2(Af[1], ps[0]);
#pragma unroll
      for (int i = 1; i < 16; i++) {
        sh0 = hfma2(Af[2 * i], ps[i], sh0);
        sh1 = hfma2(Af[2 * i + 1], ps[i], sh1);
      }
      asm volatile("" : "+r"(sh0), "+r"(sh1)::"memory");
    };
    auto epilogue = [&]() {
      wgmma_wait<0>();
      fence_regs(acc);
      fence_regs(S0); fence_regs(S1); fence_regs(S2); fence_regs(S3);
      eh0 = hmul2(bias_relu2(acc[0], bs[0]), hs[0]);
      eh1 = hmul2(bias_relu2(acc[1], bs[0]), hs[0]);
#pragma unroll
      for (int i = 1; i < 16; i++) {
        eh0 = hfma2(bias_relu2(acc[2 * i], bs[i]), hs[i], eh0);
        eh1 = hfma2(bias_relu2(acc[2 * i + 1], bs[i]), hs[i], eh1);
      }
      asm volatile("" : "+r"(eh0), "+r"(eh1)::"memory");
    };
    if (is_left) {
      if (wg == 1) named_bar_arrive(4, 256);
      const int n_elem = (last_row + 2) / kF;
      const __nv_bfloat16* lsrc = table + c * 8;
      uint32_t ia, ib, ic, id, ma;
      float lsum = 0.f, asum = 0.f;
      auto load_ix = [&](int r) {
        const int* ip = idx + min((int)blockIdx.x * 256 + tau * 8 + 2 * r + wg, n_elem - 1) * kF;
        const uint2 x = ldg64(ip), y = ldg64(ip + 2);
        ia = x.x; ib = x.y; ic = y.x; id = y.y;
      };
      auto load_row = [&](uint32_t (&v)[16], uint32_t row) {
#pragma unroll
        for (int kb = 0; kb < 4; kb++) {
          const uint4 x = ldg_row(lsrc + 32 * kb, row, true);
          v[4 * kb] = x.x; v[4 * kb + 1] = x.y; v[4 * kb + 2] = x.z; v[4 * kb + 3] = x.w;
        }
      };
      auto cvt_row = [&](uint32_t (&v)[16]) {
#pragma unroll
        for (int i = 0; i < 16; i++) v[i] = bf2h(v[i]);
      };
      auto finish = [&](bool one_row) {
        s_chain();
        sched_fence(ck, never);
        epilogue();
        fold();
        uint32_t es = hadd2((c & 1) ? eh1 : eh0, shfl_xor<1>((c & 1) ? eh0 : eh1));
        es = hadd2(es, shfl_xor<2>(es));
        const float w = one_row && (c & 1) ? 0.f : exp_e(es);
        ma = habsmax2(ma, es);
        lsum += w;
        asum = fmaf(w, h_hi(es), asum);
        sched_fence(ck, never);
      };
      ia = li01.x; ib = li01.y; ic = li23.x; id = li23.y;
      load_row(S0, ia); load_row(S1, ib); load_row(S2, ic); load_row(S3, id);
      if (wg == 0) named_bar_sync(3, 256);
#pragma unroll 1
      for (int r = 0; r < 4; r++) {
        const int e = blockIdx.x * 256 + tau * 8 + 2 * r + wg;
        load_ix(r + 1);
        lsum = 0.f; asum = 0.f; ma = 0;
        cvt_row(S0); cvt_row(S1);
        products(S0, S0, S1);
        bar_sync2<4, 5>(wg);
        issue();
        cvt_row(S2); cvt_row(S3);
        finish(true);
        products(S0, S1, S2);
        bar_sync2<4, 5>(wg);
        issue();
        load_row(S2, ic);
        finish(false);
        products(S0, S1, S3);
        bar_sync2<4, 5>(wg);
        issue();
        load_row(S0, ia); load_row(S1, ib); load_row(S3, id);
        finish(false);
        lsum += __shfl_xor_sync(0xffffffffu, lsum, 1);
        asum += __shfl_xor_sync(0xffffffffu, asum, 1);
        ma = habsmax2(ma, shfl_xor<1>(ma));
        if ((ma & 0x7fffu) > 0x7000u || ((ma >> 16) & 0x7fffu) >= 0x7c00u) lsum = __int_as_float(0x7fffffff);
        if (c == 0 && e < n_elem)
          asm volatile("{\n.reg .b64 v;\nmov.b64 v, {%1,%2};\nst.volatile.global.b64 [%0], v;\n}" ::"l"(g_left + e + ck), "f"(lsum), "f"(asum) : "memory");
      }
      if (wg == 0) named_bar_sync(4, 256);
      return;
    }
    sts128p<0>(cv_ptr, convert_f(g0[0]), v01);
    sts128p<kRow>(cv_ptr, convert_f(g0[1]), v01);
    sts128p<2 * kRow>(cv_ptr, convert_f(g0[2]), v23);
    sts128p<3 * kRow>(cv_ptr, convert_f(g0[3]), v23);
    asm volatile("{\n.reg .pred p;\nsetp.eq.u32 p, %0, 0;\n@p bar.sync 3, 256;\n@!p bar.sync 2, 128;\n}" ::"r"(wg) : "memory");

    static_for<0, 4>([&](auto Kc) {
      constexpr int kb = decltype(Kc)::value;
      const uint4 z = lds128<64 * kb>(ra[5]), x = lds128<64 * kb>(ra[0]), y = lds128<64 * kb>(ra[1]);
      S3[4 * kb] = z.x; S3[4 * kb + 1] = z.y; S3[4 * kb + 2] = z.z; S3[4 * kb + 3] = z.w;
      S0[4 * kb] = x.x; S0[4 * kb + 1] = x.y; S0[4 * kb + 2] = x.z; S0[4 * kb + 3] = x.w;
      S1[4 * kb] = y.x; S1[4 * kb + 1] = y.y; S1[4 * kb + 2] = y.z; S1[4 * kb + 3] = y.w;
      if (kb & 1) sched_fence(ck, never);
    });
#pragma unroll
    for (int i = 0; i < 16; i++) S2[i] = 0;
    static_for<0, 2>([&](auto Hc) {
      constexpr int h = decltype(Hc)::value, n = 16 / 2;
#pragma unroll
      for (int i = h * n; i < h * n + n; i++) {
        Af[2 * i] = hmul2(S0[i], S3[i]);
        Af[2 * i + 1] = hmul2(S1[i], S3[i]);
        asm volatile("" : "+r"(Af[2 * i]), "+r"(Af[2 * i + 1])::"memory");
      }
      if (h == 0) {
        if (wg == 1) named_bar_sync(5, 256);
        sched_fence(ck, never);
      }
      wgmma_fence();
#pragma unroll
      for (int s = h * n / 2; s < (h * n + n) / 2; s++) {
        const uint64_t d = dB + (uint64_t)(s * (2048 >> 4));
        if (s == 0) wgmma_rs_n128<0>(acc, Af[0], Af[1], Af[2], Af[3], d);
        else wgmma_rs_n128<1>(acc, Af[4 * s], Af[4 * s + 1], Af[4 * s + 2], Af[4 * s + 3], d);
      }
      sched_fence(ck, never);
    });
    wgmma_commit();
    bar_arrive2<5, 4>(wg);
    sched_fence(ck, never);

    auto bump = [&](uint32_t& r) { asm volatile("add.u32 %0, %0, %1;" : "+r"(r) : "n"(2 * kElem)); };
    int left = nb - 1;
    ra[0] += 2 * kElem; ra[1] += 2 * kElem; ra[5] += 2 * kElem;
    uint4 r0, r1;
    uint32_t el = wg, rdy = 0;
    auto tile = [&](auto Tc) {
      constexpr int tt = decltype(Tc)::value & 7;
      constexpr bool last = decltype(Tc)::value > 7;
      sched_fence(ck, never);
      fold();
      const uint32_t f0 = eh0, f1 = eh1;
      sts32o<(tt == 0 ? 4096 - 2 * ES_STRIDE : (tt - 1) * 1024)>(pt_ptr, eh0);
      sts32o<(tt == 0 ? 4096 - 2 * ES_STRIDE : (tt - 1) * 1024) + 512>(pt_ptr, eh1);
      if (tt == 0) mbar_arrive(sbase + OFF_BAR + 64 + 8 * el);
      if (last) bar_arrive2<13, 14, 160>(wg);
      if (tt == 2) rdy = mbar_test(sbase + OFF_BAR + 8 * min(el + 2, n_c - 1), 0);
      sched_fence(ck, never);
      if (tt == 0) load_vec(S0, ra[3]);
      if (tt == 1) load_vec(S2, ra[4]);
      if (tt == 2) load_vec(S1, ra[2]);
      if (tt == 3 && !last) {
        load_vec(S0, ra[0]);
        r0 = lds128<0>(ra[1]);
        r1 = lds128<64>(ra[1]);
      }
      if (tt == 4) {
        load_vec(S3, ra[5]);
        const uint4 v2 = lds128<128>(ra[1]), v3 = lds128<192>(ra[1]);
        S1[8] = v2.x; S1[9] = v2.y; S1[10] = v2.z; S1[11] = v2.w; S1[12] = v3.x; S1[13] = v3.y; S1[14] = v3.z; S1[15] = v3.w;
        S1[0] = r0.x; S1[1] = r0.y; S1[2] = r0.z; S1[3] = r0.w; S1[4] = r1.x; S1[5] = r1.y; S1[6] = r1.z; S1[7] = r1.w;
      }
      sched_fence(ck, never);
      s_chain();
      sched_fence(ck, never);
      epilogue();
      sched_fence(ck, never);
      if (tt == 2 && !rdy) mbar_wait(sbase + OFF_BAR + 8 * min(el + 2, n_c - 1), 0);
      if (tt == 0) { products(S1, S3, S0); bump(ra[3]); }
      if (tt == 1) { products(S1, S0, S2); bump(ra[4]); }
      if (tt == 2) { products(S0, S2, S1); bump(ra[2]); }
      if (tt == 3) products(S1, S2, S3);
      if (tt == 4) {
        products(S0, S1, S3);
        bump(ra[0]); bump(ra[1]); bump(ra[5]);
        asm volatile("add.u32 %0, %0, %1;" : "+r"(pt_ptr) : "n"(2 * ES_STRIDE));
        el += 2;
      }
      sched_fence(ck, never);
      keep2(ck, f0, f1, never);
      bar_sync2<4, 5>(wg);
      issue();
    };
#pragma unroll 1
    for (;;) {
      tile(std::integral_constant<int, 0>{});
      tile(std::integral_constant<int, 1>{});
      tile(std::integral_constant<int, 2>{});
      if (left == 0) break;
      tile(std::integral_constant<int, 3>{});
      tile(std::integral_constant<int, 4>{});
      left--;
    }
    tile(std::integral_constant<int, 8 + 3>{});
    sched_fence(ck, never);
    fold();
    sts32o<3072>(pt_ptr, eh0);
    sts32o<3072 + 512>(pt_ptr, eh1);
    bar_arrive2<10, 11, 160>(wg);
    s_chain();
    sched_fence(ck, never);
    epilogue();
    sched_fence(ck, never);
    fold();
    sts32o<4096>(pt_ptr + ck, eh0);
    sts32o<4096 + 512>(pt_ptr, eh1);
    bar_arrive2<8, 9, 160>(wg);
    sched_fence(ck, never);
    if (wg == 0) {
      named_bar_sync(4, 256);
    } else if (n_c & 1) {
      for (int i = 0; i < 5; i++) {
        named_bar_sync(5, 256);
        named_bar_arrive(4, 256);
      }
    }
  } else {
    {
      asm volatile("setmaxnreg.dec.sync.aligned.u32 104;");
      uint4 wr[16];
#pragma unroll
      for (int r = 0; r < 16; r++) wr[r] = ldg128(W + (32 * wq + 2 * r) * kD + 8 * lane);
      const uint32_t wa = sbase + OFF_B + ((lane >> 3) & 1) * B_NBLK + wq * 4096 + (lane >> 4) * 128;
      const uint32_t lx = (lane & 7) ^ (lane >> 4);
      uint32_t wad[4], mw = 0;
#pragma unroll
      for (int x = 0; x < 4; x++) wad[x] = wa + ((lx ^ (2 * x)) << 4);
      sched_fence(ck, never);
      static_for<0, 16>([&](auto Rc) {
        constexpr int r = decltype(Rc)::value;
        uint4 v;
        v.x = bf2h_x16(wr[r].x); v.y = bf2h_x16(wr[r].y); v.z = bf2h_x16(wr[r].z); v.w = bf2h_x16(wr[r].w);
        sts128<(r & 3) * 1024 + (r >> 2) * 256>(wad[r >> 2], v);
        mw = babsmax2(babsmax2(mw, wr[r].x), babsmax2(wr[r].y, babsmax2(wr[r].z, wr[r].w)));
        if (r == 3) sched_fence(ck, never);
        if (r == 7 || r == 11) sched_fence(ck, never);
      });
      sched_fence(ck, never);
      fence_proxy_async();
      named_bar_arrive(3, 256);
      sched_fence(ck, never);
      sts32p(sbase + OFF_STAT + wq * 4 + ck, redux_max(absmax_bits(mw)), lane == 0);
    }
    asm volatile("setmaxnreg.dec.sync.aligned.u32 %0;" ::"n"(504 - 2 * 216));
    if ((int)blockIdx.x >= n_left) helper_rest(idx, table, W, late, base_cnt, extra, last_row, n_left, smem);
    else {
      named_bar_sync(6, 160);
#pragma unroll 1
      for (int q = 2; q < 8; q++) {
        const int e = min((int)blockIdx.x * 256 + (t >> 2) * 8 + q, (last_row + 2) / kF - 1);
        const uint32_t row = ldg32(idx + e * kF + (t & 3));
        asm volatile("prefetch.global.L2 [%0];\nprefetch.global.L2 [%0+128];" ::"l"(table + (size_t)row * kD) : "memory");
      }
    }
  }
}

}

extern "C" void kernel_launch(void* const* d_in, const int* in_sizes, int n_in, void* d_out, int out_size) {
  const int* idx = (const int*)d_in[0];
  const __nv_bfloat16* table = (const __nv_bfloat16*)d_in[1];
  const int* ii = (const int*)d_in[2];
  const int* jj = (const int*)d_in[3];
  const __nv_bfloat16* W = (const __nv_bfloat16*)d_in[4];
  const __nv_bfloat16* bias = (const __nv_bfloat16*)d_in[5];
  const __nv_bfloat16* hvec = (const __nv_bfloat16*)d_in[6];
  const __nv_bfloat16* pvec = (const __nv_bfloat16*)d_in[7];
  __nv_bfloat16* out = (__nv_bfloat16*)d_out;
  const int B = out_size;

  static int num_sms = 0;
  if (num_sms == 0) {
    int dev = 0;
    cudaGetDevice(&dev);
    cudaDeviceGetAttribute(&num_sms, cudaDevAttrMultiProcessorCount, dev);
    cudaFuncSetAttribute(afm_kernel, cudaFuncAttributeMaxDynamicSharedMemorySize, SMEM_BYTES);
  }
  const Sched sched = {{
    0x2d2cb011u, 0x2c9a0662u, 0x2876c228u, 0x26074141u, 0x2655c878u, 0x2985dc43u, 0x18722403u, 0x22299aaeu,
    0x02a6b0b1u, 0x30d73d00u, 0x00941af1u, 0x2ee29c4au, 0x2ad5a410u, 0x21250923u, 0x328a84aeu, 0x0d780599u,
    0x324551f8u, 0x3112a583u, 0x062ca4eeu, 0x155360e3u, 0x1cb204d6u, 0x1f4280c9u, 0x2776e487u, 0x090b60a2u,
    0x2413bf17u, 0x168b28ecu, 0x10c78a70u, 0x2f578ed1u, 0x1a334ac2u, 0x0888c875u, 0x1d5a3249u, 0x2305bf2au
  }};
  for (int off = 0; off < B; off += kMaxChunk) {
    const int n = B - off < kMaxChunk ? B - off : kMaxChunk;
    const int n_left = (n + 255) / 256;
    int n_main = num_sms - n_left;
    if (n_main > n) n_main = n;
    if (n_main < (n + kMaxB - 1) / kMaxB) n_main = (n + kMaxB - 1) / kMaxB;
    const Late late = {{bias, hvec, pvec, pvec}, ii, jj, out + off, sched};
    afm_kernel<<<n_left + n_main, kThreads, SMEM_BYTES>>>(idx + (size_t)off * kF, table, W, n / n_main, n % n_main,
                                                          n * kF - 2, n_left, late);
  }
}
```

```cpp
#include <cuda_runtime.h>
#include <cuda_bf16.h>
#include <cuda_fp16.h>
#include <stdint.h>
#include <type_traits>

namespace {

constexpr int kF = 26;
constexpr int kD = 128;
constexpr int kP = 325;
constexpr int kMaxB = 8;
constexpr int kThreads = 384;
constexpr int kRow = 320;
constexpr int kElem = kF * kRow;

constexpr int B_NBLK = 16 * 1024;
constexpr int OFF_B = 0;
constexpr int OFF_EMB = 2 * B_NBLK;
constexpr int OFF_ES = OFF_EMB + kMaxB * kElem;
constexpr int ES_STRIDE = 5 * 1024;
constexpr int OFF_VEC = OFF_ES + (kMaxB + 2) * ES_STRIDE;
constexpr int OFF_STAT = OFF_VEC + 768;
constexpr int OFF_BAR = OFF_STAT + 128;
constexpr int SMEM_USED = OFF_BAR + 128;
static_assert(OFF_EMB + (kMaxB + 2) * kElem <= SMEM_USED, "unused operand prefetches run up to 2 elements past the end");
constexpr int SMEM_BYTES = SMEM_USED;
static_assert(OFF_ES % 16 == 0 && OFF_VEC % 16 == 0 && OFF_STAT % 16 == 0 && kElem % 128 == 0, "alignment");

struct Sched { uint32_t e[32]; };
struct Late {
  const __nv_bfloat16* vec[4];
  const int* ii;
  const int* jj;
  __nv_bfloat16* out;
  Sched sched;
};

constexpr int kMaxChunk = 8192;
__device__ float2 g_left[kMaxChunk];

__device__ __forceinline__ uint32_t smem_u32(const void* p) { return (uint32_t)__cvta_generic_to_shared(p); }
__device__ __forceinline__ void named_bar_sync(int id, int n) { asm volatile("bar.sync %0, %1;" ::"r"(id), "r"(n) : "memory"); }
__device__ __forceinline__ void named_bar_arrive(int id, int n) { asm volatile("bar.arrive %0, %1;" ::"r"(id), "r"(n) : "memory"); }
template <int A, int B>
__device__ __forceinline__ void bar_sync2(uint32_t sel) {
  asm volatile("{\n.reg .pred p;\nsetp.eq.u32 p, %0, 0;\n@p bar.sync %1, 256;\n@!p bar.sync %2, 256;\n}" ::"r"(sel), "n"(A), "n"(B) : "memory");
}
template <int A, int B, int N = 256>
__device__ __forceinline__ void bar_arrive2(uint32_t sel) {
  asm volatile("{\n.reg .pred p;\nsetp.eq.u32 p, %0, 0;\n@p bar.arrive %1, %3;\n@!p bar.arrive %2, %3;\n}" ::"r"(sel), "n"(A), "n"(B), "n"(N) : "memory");
}
__device__ __forceinline__ void mbar_init(uint32_t bar, uint32_t count) {
  asm volatile("mbarrier.init.shared::cta.b64 [%0], %1;" ::"r"(bar), "r"(count) : "memory");
}
__device__ __forceinline__ void mbar_arrive(uint32_t bar) {
  asm volatile("mbarrier.arrive.shared::cta.b64 _, [%0];" ::"r"(bar) : "memory");
}
__device__ __forceinline__ void mbar_arrive_p(uint32_t bar, bool on) {
  asm volatile("{\n.reg .pred p;\nsetp.ne.u32 p, %1, 0;\n@p mbarrier.arrive.shared::cta.b64 _, [%0];\n}" ::"r"(bar), "r"((uint32_t)on) : "memory");
}
__device__ __forceinline__ uint32_t mbar_test(uint32_t bar, uint32_t parity) {
  uint32_t ok;
  asm volatile("{\n.reg .pred p;\nmbarrier.test_wait.parity.shared::cta.b64 p, [%1], %2;\nselp.u32 %0, 1, 0, p;\n}\n"
               : "=r"(ok) : "r"(bar), "r"(parity) : "memory");
  return ok;
}
__device__ __forceinline__ void mbar_wait(uint32_t bar, uint32_t parity) {
  uint32_t ok, it = 0;
  do {
    asm volatile("{\n.reg .pred p;\nmbarrier.try_wait.parity.shared::cta.b64 p, [%1], %2, %3;\nselp.u32 %0, 1, 0, p;\n}\n"
                 : "=r"(ok) : "r"(bar), "r"(parity), "r"(20000) : "memory");
  } while (!ok && ++it < (1u << 16));
}
__device__ __forceinline__ void wgmma_fence() { asm volatile("wgmma.fence.sync.aligned;" ::: "memory"); }
__device__ __forceinline__ void wgmma_commit() { asm volatile("wgmma.commit_group.sync.aligned;" ::: "memory"); }
template <int N>
__device__ __forceinline__ void wgmma_wait() { asm volatile("wgmma.wait_group.sync.aligned %0;" ::"n"(N) : "memory"); }
__device__ __forceinline__ void fence_proxy_async() { asm volatile("fence.proxy.async.shared::cta;" ::: "memory"); }

__device__ __forceinline__ uint32_t hmul2(uint32_t a, uint32_t b) {
  uint32_t d;
  asm("mul.rn.f16x2 %0, %1, %2;" : "=r"(d) : "r"(a), "r"(b));
  return d;
}
__device__ __forceinline__ uint32_t hadd2(uint32_t a, uint32_t b) {
  uint32_t d;
  asm("add.rn.f16x2 %0, %1, %2;" : "=r"(d) : "r"(a), "r"(b));
  return d;
}
__device__ __forceinline__ uint32_t hfma2(uint32_t a, uint32_t b, uint32_t c) {
  uint32_t d;
  asm("fma.rn.f16x2 %0, %1, %2, %3;" : "=r"(d) : "r"(a), "r"(b), "r"(c));
  return d;
}
__device__ __forceinline__ uint32_t bias_relu2(uint32_t x, uint32_t nb) {
  uint32_t d;
  asm("max.NaN.f16x2 %0, %1, %2;" : "=r"(d) : "r"(x), "r"(nb));
  return d;
}
__device__ __forceinline__ uint32_t habsmax2(uint32_t a, uint32_t b) {
  uint32_t d;
  asm("max.NaN.xorsign.abs.f16x2 %0, %1, %2;" : "=r"(d) : "r"(a), "r"(b));
  return d;
}
__device__ __forceinline__ uint32_t babsmax2(uint32_t a, uint32_t b) {
  uint32_t d;
  asm("max.NaN.xorsign.abs.bf16x2 %0, %1, %2;" : "=r"(d) : "r"(a), "r"(b));
  return d;
}
__device__ __forceinline__ uint32_t bf2h(uint32_t x) {
  uint32_t d;
  asm("cvt.rn.f16x2.f32 %0, %1, %2;" : "=r"(d) : "f"(__uint_as_float(x & 0xffff0000u)), "f"(__uint_as_float(x << 16)));
  return d;
}
__device__ __forceinline__ uint32_t bf2h_x16(uint32_t x) {
  uint32_t hi, lo, d;
  asm("fma.rn.bf16x2 %0, %1, %2, %3;" : "=r"(hi) : "r"(x), "r"(0x41800000u), "r"(0u));
  asm("{\n.reg .b16 l, h;\n.reg .b32 t;\nmov.b32 {l, h}, %1;\nmov.b32 t, {l, l};\nfma.rn.bf16x2 %0, t, %2, %3;\n}"
      : "=r"(lo) : "r"(x), "r"(0x41800000u), "r"(0u));
  asm("cvt.rn.f16x2.f32 %0, %1, %2;" : "=r"(d) : "f"(__uint_as_float(hi)), "f"(__uint_as_float(lo)));
  return d;
}
template <bool HI_FMA>
__device__ __forceinline__ uint32_t bf2h_f(uint32_t x) {
  uint32_t hi = x & 0xffff0000u, lo, d;
  if (HI_FMA) asm("fma.rn.bf16x2 %0, %1, %2, %3;" : "=r"(hi) : "r"(x), "r"(0x3f800000u), "r"(0u));
  asm("{\n.reg .b16 l, h;\n.reg .b32 t;\nmov.b32 {l, h}, %1;\nmov.b32 t, {l, l};\nfma.rn.bf16x2 %0, t, %2, %3;\n}"
      : "=r"(lo) : "r"(x), "r"(0x3f800000u), "r"(0u));
  asm("cvt.rn.f16x2.f32 %0, %1, %2;" : "=r"(d) : "f"(__uint_as_float(hi)), "f"(__uint_as_float(lo)));
  return d;
}
__device__ __forceinline__ uint4 convert(uint4 v) { return make_uint4(bf2h(v.x), bf2h(v.y), bf2h(v.z), bf2h(v.w)); }
__device__ __forceinline__ uint4 convert_f(uint4 v) {
  return make_uint4(bf2h_f<false>(v.x), bf2h_f<true>(v.y), bf2h_f<false>(v.z), bf2h_f<true>(v.w));
}
__device__ __forceinline__ float h_lo(uint32_t x) { return __half2float(__ushort_as_half((unsigned short)(x & 0xffffu))); }
__device__ __forceinline__ float h_hi(uint32_t x) { return __half2float(__ushort_as_half((unsigned short)(x >> 16))); }
__device__ __forceinline__ uint32_t redux_max(uint32_t v) {
  uint32_t d;
  asm volatile("redux.sync.max.u32 %0, %1, 0xffffffff;" : "=r"(d) : "r"(v));
  return d;
}
__device__ __forceinline__ uint32_t absmax_bits(uint32_t m) { return max(m & 0x7fffu, (m >> 16) & 0x7fffu); }

template <int OFF>
__device__ __forceinline__ uint4 lds128(uint32_t addr) {
  uint4 v;
  asm volatile("ld.shared.v4.u32 {%0,%1,%2,%3}, [%4+%5];" : "=r"(v.x), "=r"(v.y), "=r"(v.z), "=r"(v.w) : "r"(addr), "n"(OFF));
  return v;
}
template <int OFF>
__device__ __forceinline__ void sts128(uint32_t addr, uint4 v) {
  asm volatile("st.shared.v4.u32 [%0+%5], {%1,%2,%3,%4};" ::"r"(addr), "r"(v.x), "r"(v.y), "r"(v.z), "r"(v.w), "n"(OFF) : "memory");
}
__device__ __forceinline__ uint32_t lds32(uint32_t addr) {
  uint32_t v;
  asm volatile("ld.shared.u32 %0, [%1];" : "=r"(v) : "r"(addr));
  return v;
}
__device__ __forceinline__ void sts32(uint32_t addr, uint32_t v) { asm volatile("st.shared.u32 [%0], %1;" ::"r"(addr), "r"(v) : "memory"); }
__device__ __forceinline__ uint32_t ldg32(const void* p) {
  uint32_t v;
  asm volatile("ld.global.u32 %0, [%1];" : "=r"(v) : "l"(p) : "memory");
  return v;
}
__device__ __forceinline__ uint4 ldg128(const void* p) {
  uint4 v;
  asm volatile("ld.global.v4.u32 {%0,%1,%2,%3}, [%4];" : "=r"(v.x), "=r"(v.y), "=r"(v.z), "=r"(v.w) : "l"(p) : "memory");
  return v;
}
__device__ __forceinline__ uint2 ldg64(const void* p) {
  uint2 v;
  asm volatile("ld.global.v2.u32 {%0,%1}, [%2];" : "=r"(v.x), "=r"(v.y) : "l"(p) : "memory");
  return v;
}
__device__ __forceinline__ uint2 ldg64p(const void* p, bool on) {
  uint2 v;
  asm volatile("{\n.reg .pred p;\nsetp.ne.u32 p, %3, 0;\n@p ld.volatile.global.v2.u32 {%0,%1}, [%2];\n}" : "=r"(v.x), "=r"(v.y) : "l"(p), "r"((uint32_t)on) : "memory");
  return v;
}
__device__ __forceinline__ void ldg_idx4(uint2& x, uint2& y, const void* base, uint32_t off, bool on0, bool on1) {
  asm volatile("{\n.reg .pred p, q;\n.reg .b64 a;\n.reg .b32 lo, hi;\nsetp.ne.u32 p, %6, 0;\nsetp.ne.u32 q, %7, 0;\n"
               "mov.b64 {lo, hi}, %4;\nadd.cc.u32 lo, lo, %5;\naddc.u32 hi, hi, 0;\nmov.b64 a, {lo, hi};\n"
               "@p ld.volatile.global.v2.u32 {%0,%1}, [a];\n@q ld.volatile.global.v2.u32 {%2,%3}, [a+8];\n}"
               : "=r"(x.x), "=r"(x.y), "=r"(y.x), "=r"(y.y) : "l"(base), "r"(off), "r"((uint32_t)on0), "r"((uint32_t)on1) : "memory");
}
__device__ __forceinline__ uint4 ldg_row(const void* base, uint32_t row, bool on) {
  uint4 v;
  asm volatile("{\n.reg .pred p;\n.reg .b64 a;\nsetp.ne.u32 p, %6, 0;\nmad.wide.u32 a, %5, 256, %4;\n@p ld.global.v4.u32 {%0,%1,%2,%3}, [a];\n}"
               : "=r"(v.x), "=r"(v.y), "=r"(v.z), "=r"(v.w) : "l"(base), "r"(row), "r"((uint32_t)on) : "memory");
  return v;
}
template <int OFF>
__device__ __forceinline__ void sts128p(uint32_t addr, uint4 v, bool on) {
  asm volatile("{\n.reg .pred p;\nsetp.ne.u32 p, %6, 0;\n@p st.shared.v4.u32 [%0+%5], {%1,%2,%3,%4};\n}"
               ::"r"(addr), "r"(v.x), "r"(v.y), "r"(v.z), "r"(v.w), "n"(OFF), "r"((uint32_t)on) : "memory");
}
__device__ __forceinline__ void sts32p(uint32_t addr, uint32_t v, bool on) {
  asm volatile("{\n.reg .pred p;\nsetp.ne.u32 p, %2, 0;\n@p st.shared.u32 [%0], %1;\n}" ::"r"(addr), "r"(v), "r"((uint32_t)on) : "memory");
}
__device__ __forceinline__ uint32_t shfl_xor_v(uint32_t v, int m) {
  uint32_t d;
  asm volatile("shfl.sync.bfly.b32 %0, %1, %2, 0x1f, 0xffffffff;" : "=r"(d) : "r"(v), "r"(m));
  return d;
}
template <int M>
__device__ __forceinline__ uint32_t shfl_xor(uint32_t v) {
  uint32_t d;
  asm volatile("shfl.sync.bfly.b32 %0, %1, %2, 0x1f, 0xffffffff;" : "=r"(d) : "r"(v), "n"(M));
  return d;
}
template <int I, int N, typename F>
__device__ __forceinline__ void static_for(F&& f) {
  if constexpr (I < N) {
    f(std::integral_constant<int, I>{});
    static_for<I + 1, N>(f);
  }
}
template <int N>
__device__ __forceinline__ void fence_regs(uint32_t (&r)[N]) {
#pragma unroll
  for (int i = 0; i < N; i++) asm volatile("" : "+r"(r[i])::"memory");
}
__device__ __forceinline__ void load_vec(uint32_t (&v)[16], uint32_t a) {
  const uint4 v0 = lds128<0>(a), v1 = lds128<64>(a), v2 = lds128<128>(a), v3 = lds128<192>(a);
  v[0] = v0.x; v[1] = v0.y; v[2] = v0.z; v[3] = v0.w; v[4] = v1.x; v[5] = v1.y; v[6] = v1.z; v[7] = v1.w;
  v[8] = v2.x; v[9] = v2.y; v[10] = v2.z; v[11] = v2.w; v[12] = v3.x; v[13] = v3.y; v[14] = v3.z; v[15] = v3.w;
}

template <int OFF>
__device__ __forceinline__ void sts32o(uint32_t addr, uint32_t v) {
  asm volatile("st.shared.u32 [%0+%2], %1;" ::"r"(addr), "r"(v), "n"(OFF) : "memory");
}
__device__ __forceinline__ void keep2(uint32_t& ck, uint32_t a, uint32_t b, uint32_t never) {
  asm volatile("{\n.reg .pred p;\nsetp.ne.u32 p, %3, 0;\n@p xor.b32 %0, %1, %2;\n}" : "+r"(ck) : "r"(a), "r"(b), "r"(never));
}
__device__ __forceinline__ float exp_e(uint32_t es) {
  float w;
  asm("ex2.approx.ftz.f32 %0, %1;" : "=f"(w) : "f"(h_lo(es) * (1.4426950408889634f / 256.f)));
  return w;
}
__device__ __forceinline__ uint32_t clock32() {
  uint32_t v;
  asm volatile("mov.u32 %0, %%clock;" : "=r"(v)::"memory");
  return v;
}
__device__ __forceinline__ void sched_fence(uint32_t& ck, uint32_t never) {
  asm volatile("{\n.reg .pred p;\nsetp.ne.u32 p, %1, 0;\n@p mov.u32 %0, %%clock;\n}" : "+r"(ck) : "r"(never) : "memory");
}

template <int ACCUM>
__device__ __forceinline__ void wgmma_rs_n128(uint32_t (&d)[32], uint32_t a0, uint32_t a1, uint32_t a2, uint32_t a3, uint64_t descB) {
  if (ACCUM == 1) {
    asm volatile(
        "wgmma.mma_async.sync.aligned.m64n128k16.f16.f16.f16 "
        "{%0, %1, %2, %3, %4, %5, %6, %7, %8, %9, %10, %11, %12, %13, %14, %15, %16, %17, %18, %19, %20, %21, %22, %23, %24, %25, %26, %27, %28, %29, %30, %31}, "
        "{%32, %33, %34, %35}, %36, 1, 1, 1, 1;\n"
        : "+r"(d[0]), "+r"(d[1]), "+r"(d[2]), "+r"(d[3]), "+r"(d[4]), "+r"(d[5]), "+r"(d[6]), "+r"(d[7]), "+r"(d[8]), "+r"(d[9]), "+r"(d[10]), "+r"(d[11]), "+r"(d[12]), "+r"(d[13]), "+r"(d[14]), "+r"(d[15]), "+r"(d[16]), "+r"(d[17]), "+r"(d[18]), "+r"(d[19]), "+r"(d[20]), "+r"(d[21]), "+r"(d[22]), "+r"(d[23]), "+r"(d[24]), "+r"(d[25]), "+r"(d[26]), "+r"(d[27]), "+r"(d[28]), "+r"(d[29]), "+r"(d[30]), "+r"(d[31])
        : "r"(a0), "r"(a1), "r"(a2), "r"(a3), "l"(descB));
  }
  if (ACCUM == 0) {
    asm volatile(
        "wgmma.mma_async.sync.aligned.m64n128k16.f16.f16.f16 "
        "{%0, %1, %2, %3, %4, %5, %6, %7, %8, %9, %10, %11, %12, %13, %14, %15, %16, %17, %18, %19, %20, %21, %22, %23, %24, %25, %26, %27, %28, %29, %30, %31}, "
        "{%32, %33, %34, %35}, %36, 0, 1, 1, 1;\n"
        : "=r"(d[0]), "=r"(d[1]), "=r"(d[2]), "=r"(d[3]), "=r"(d[4]), "=r"(d[5]), "=r"(d[6]), "=r"(d[7]), "=r"(d[8]), "=r"(d[9]), "=r"(d[10]), "=r"(d[11]), "=r"(d[12]), "=r"(d[13]), "=r"(d[14]), "=r"(d[15]), "=r"(d[16]), "=r"(d[17]), "=r"(d[18]), "=r"(d[19]), "=r"(d[20]), "=r"(d[21]), "=r"(d[22]), "=r"(d[23]), "=r"(d[24]), "=r"(d[25]), "=r"(d[26]), "=r"(d[27]), "=r"(d[28]), "=r"(d[29]), "=r"(d[30]), "=r"(d[31])
        : "r"(a0), "r"(a1), "r"(a2), "r"(a3), "l"(descB));
  }
}

__device__ __forceinline__ float rbf(float x) { return __bfloat162float(__float2bfloat16_rn(x)); }
__device__ __forceinline__ float warp_sum(float v) {
#pragma unroll
  for (int o = 16; o > 0; o >>= 1) v += __shfl_xor_sync(0xffffffffu, v, o);
  return v;
}

__device__ __noinline__ void general_element(const int* __restrict__ idx, const __nv_bfloat16* __restrict__ table,
                                             const int* __restrict__ ii, const int* __restrict__ jj,
                                             const __nv_bfloat16* __restrict__ W, const __nv_bfloat16* __restrict__ bias,
                                             const __nv_bfloat16* __restrict__ hvec, const __nv_bfloat16* __restrict__ pvec,
                                             __nv_bfloat16* __restrict__ out, float* ev) {
  const int lane = threadIdx.x & 31;
  auto pair4 = [&](int p, float (&pr)[4]) {
    const __nv_bfloat16* a = table + (size_t)idx[ii[p]] * kD + 4 * lane;
    const __nv_bfloat16* b = table + (size_t)idx[jj[p]] * kD + 4 * lane;
#pragma unroll
    for (int q = 0; q < 4; q++) pr[q] = rbf(__bfloat162float(a[q]) * __bfloat162float(b[q]));
  };
  float m = -INFINITY;
  bool has_nan = false;
  for (int p = 0; p < kP; p++) {
    float pr[4], x[4] = {0.f, 0.f, 0.f, 0.f};
    pair4(p, pr);
    for (int l = 0; l < 32; l++) {
#pragma unroll
      for (int q = 0; q < 4; q++) {
        const float v = __shfl_sync(0xffffffffu, pr[q], l);
        const uint2 w = *reinterpret_cast<const uint2*>(W + (4 * l + q) * kD + 4 * lane);
        x[0] = fmaf(v, __uint_as_float(w.x << 16), x[0]);
        x[1] = fmaf(v, __uint_as_float(w.x & 0xffff0000u), x[1]);
        x[2] = fmaf(v, __uint_as_float(w.y << 16), x[2]);
        x[3] = fmaf(v, __uint_as_float(w.y & 0xffff0000u), x[3]);
      }
    }
    float e = 0.f;
#pragma unroll
    for (int q = 0; q < 4; q++) {
      const float y = rbf(rbf(x[q]) + __bfloat162float(bias[4 * lane + q]));
      e = fmaf(rbf(0.5f * rbf(y + fabsf(y))), __bfloat162float(hvec[4 * lane + q]), e);
    }
    e = rbf(warp_sum(e));
    has_nan |= (e != e);
    m = fmaxf(m, e);
    if (lane == 0) ev[p] = e;
  }
  __syncwarp();
  float l = 0.f;
  for (int p = lane; p < kP; p += 32) l += expf(ev[p] - m);
  l = warp_sum(l);
  float pooled[4] = {0.f, 0.f, 0.f, 0.f};
  for (int p = 0; p < kP; p++) {
    float pr[4];
    pair4(p, pr);
    const float al = rbf(expf(ev[p] - m) / l);
#pragma unroll
    for (int q = 0; q < 4; q++) pooled[q] = fmaf(al, pr[q], pooled[q]);
  }
  float o = 0.f;
#pragma unroll
  for (int q = 0; q < 4; q++) o = fmaf(rbf(pooled[q]), __bfloat162float(pvec[4 * lane + q]), o);
  o = warp_sum(o);
  if (has_nan) o = __int_as_float(0x7fffffff);
  if (lane == 0) *out = __float2bfloat16_rn(o);
}

__device__ __forceinline__ void helper_rest(const int* __restrict__ idx, const __nv_bfloat16* __restrict__ table,
                                            const __nv_bfloat16* __restrict__ W, const Late& late, int per, int n_elem,
                                            int n_left, uint8_t* smem) {
  constexpr uint32_t sbase = 0x400u;
  uint32_t tid, cta;
  asm volatile("mov.u32 %0, %%tid.x;\nmov.u32 %1, %%ctaid.x;" : "=r"(tid), "=r"(cta));
  const int t = tid & 127, lane = tid & 31, wq = (tid >> 5) & 3;
  cta -= n_left;
  const int b0 = cta * per, last_row = n_elem * kF - 2;
  const int n_out = min(per, n_elem - b0), n_c = max(n_out, 2);
  const int grp = 7 - (t >> 4);
  const bool v01 = grp < 7, v23 = grp < 6;
  int irow = (b0 + (n_c > 2 ? 2 : 0)) * kF + 4 * grp;
  uint2 gi01 = ldg64(idx + min(irow, last_row));
  uint2 gi23 = ldg64(idx + min(irow + 2, last_row));
  const __nv_bfloat16* gsrc = table + (t & 15) * 8;
  uint32_t cv_ptr = sbase + OFF_EMB + 2 * kElem + 4 * grp * kRow + (t & 15) * 16;
  uint32_t me = 0, ck = 0;
  auto track = [&](const uint4& a, const uint4& b, bool on) {
    const uint32_t m = babsmax2(babsmax2(babsmax2(a.x, a.y), babsmax2(a.z, a.w)), babsmax2(babsmax2(b.x, b.y), babsmax2(b.z, b.w)));
    me = babsmax2(me, on ? m : 0u);
  };
  named_bar_sync(6, 160);
#pragma unroll 1
  for (int e = 2; e < n_c + 2; e++) {
    const uint4 g0 = ldg_row(gsrc, gi01.x, v01), g1 = ldg_row(gsrc, gi01.y, v01);
    const uint4 g2 = ldg_row(gsrc, gi23.x, v23), g3 = ldg_row(gsrc, gi23.y, v23);
    irow += e + 1 == n_c ? (1 - n_c) * kF : kF;
    gi01 = ldg64(idx + min(irow, last_row));
    gi23 = ldg64(idx + min(irow + 2, last_row));
    uint4 h0 = convert(g0), h1 = convert(g1), h2 = convert(g2), h3 = convert(g3);
    asm volatile("" : "+r"(h0.x), "+r"(h0.y), "+r"(h0.z), "+r"(h0.w), "+r"(h1.x), "+r"(h1.y), "+r"(h1.z), "+r"(h1.w),
                      "+r"(h2.x), "+r"(h2.y), "+r"(h2.z), "+r"(h2.w), "+r"(h3.x), "+r"(h3.y), "+r"(h3.z), "+r"(h3.w));
    sched_fence(ck, tid >> 10);
    sts128p<0>(cv_ptr, h0, v01 && e < n_c);
    sts128p<kRow>(cv_ptr, h1, v01 && e < n_c);
    sts128p<2 * kRow>(cv_ptr, h2, v23 && e < n_c);
    sts128p<3 * kRow>(cv_ptr, h3, v23 && e < n_c);
    __syncwarp();
    mbar_arrive_p(sbase + OFF_BAR + 8 * e, lane == 0 && e < n_c);
    sched_fence(ck, tid >> 10);
    cv_ptr += kElem;
    track(g0, g1, v01);
    track(g2, g3, v23);
  }
  bool ok_cta;
  float ds;
  {
    const uint32_t s0 = ldg32(late.vec[t >> 6] + 2 * (t & 63)), s1 = ldg32(late.vec[2] + 2 * (t & 63));
    const uint32_t s2 = ldg32(late.vec[(t >> 6) ^ 1] + 2 * (t & 63));
    uint32_t pi[3], pj[3];
#pragma unroll
    for (int r = 0; r < 3; r++) {
      pi[r] = ldg32(late.ii + min(t + 128 * r, kP - 1));
      pj[r] = ldg32(late.jj + min(t + 128 * r, kP - 1));
    }
    float v0 = 16.f * (fabsf(__uint_as_float(s0 << 16)) + fabsf(__uint_as_float(s0 & 0xffff0000u)));
    float v1 = 16.f * (fabsf(__uint_as_float(s1 << 16)) + fabsf(__uint_as_float(s1 & 0xffff0000u)));
    if (t >= 64) v1 = fabsf(__uint_as_float(s0 << 16) * __uint_as_float(s2 << 16)) +
                      fabsf(__uint_as_float(s0 & 0xffff0000u) * __uint_as_float(s2 & 0xffff0000u));
    bool good = true;
#pragma unroll
    for (int r = 0; r < 3; r++)
      good &= (pi[r] < pj[r]) & (pj[r] < kF) & (((pi[r] * (2 * kF - 1 - pi[r])) >> 1) + pj[r] - pi[r] - 1 == min(t + 128 * r, kP - 1));
    if (!good) v0 = __int_as_float(0x7fffffff);
    v0 = warp_sum(v0);
    v1 = warp_sum(v1);
    sts32p(sbase + OFF_STAT + 64 + wq * 4, __float_as_uint(v0), lane == 0);
    sts32p(sbase + OFF_STAT + 80 + wq * 4, __float_as_uint(v1), lane == 0);
    sts32p(sbase + OFF_STAT + 16 + wq * 4 + ck, redux_max(absmax_bits(me)), lane == 0);
    named_bar_sync(6, 128);
    const uint32_t st = lds32(sbase + OFF_STAT + lane * 4);
    const float Wm = 2048.f * __uint_as_float(redux_max(lane < 4 ? st : 0u) << 16);
    const float M = __uint_as_float(redux_max(lane >= 4 && lane < 8 ? st : 0u) << 16);
    const float sp = __uint_as_float(st) + __shfl_xor_sync(0xffffffffu, __uint_as_float(st), 1);
    const float Bs = __shfl_sync(0xffffffffu, sp, 16);
    const float Hs = __shfl_sync(0xffffffffu, sp, 18);
    const float Ps = __shfl_sync(0xffffffffu, sp, 20);
    const float HB = __shfl_sync(0xffffffffu, sp, 22);
    const float M2 = M * M, X = fmaf(M2, Wm, Bs), G = fmaf(2.f, M, 1.f);
    constexpr float u = 1.f / 33554432.f;
    const float de = u * (Hs * (Wm * G + 128.f * M2 + 16.f) + 128.f * X + 256.f);
    ds = u * (Ps * G + 128.f * M2 + 256.f);
    ok_cta = M2 <= 60000.f && Wm <= 128.f * 60000.f && X <= 60000.f && Hs <= 60000.f && Ps <= 60000.f && de <= 1.f && HB <= 64.f;
  }
#pragma unroll 1
  for (int e = wq; e < n_c; e += 4) {
    const uint32_t ea = sbase + OFF_ES + (2 + e) * ES_STRIDE + lane * 16;
    float l = 0.f, a = 0.f;
    if (lane == 0 && e < n_out) {
      float2* const gp = g_left + b0 + e;
      for (uint32_t it = 0; it < (1u << 22); it++) {
        asm volatile("{\n.reg .b64 v;\nld.volatile.global.b64 v, [%2];\nmov.b64 {%0,%1}, v;\n}" : "=f"(l), "=f"(a) : "l"(gp) : "memory");
        if (__float_as_uint(l) != 0u) break;
        __nanosleep(200);
      }
      asm volatile("st.volatile.global.b64 [%0], %1;" ::"l"(gp), "l"(0ull) : "memory");
    }
    __syncwarp();
    uint32_t mx = lane == 0 && !(l > 0.f) ? 0x7fffu : 0u;
    auto take = [&](const uint4& v) {
      const uint32_t es = hadd2(hadd2(v.x, v.y), hadd2(v.z, v.w));
      const float w = exp_e(es);
      mx = habsmax2(mx, es);
      l += w;
      a = fmaf(w, h_hi(es), a);
    };
    const bool last = e + 2 >= n_c;
    if (last) named_bar_sync(13 + (e & 1), 160);
    else mbar_wait(sbase + OFF_BAR + 80 + 8 * e, 0);
    {
      uint4 v[6];
      static_for<0, 6>([&](auto Qc) { v[decltype(Qc)::value] = lds128<decltype(Qc)::value * 512>(ea); });
      sched_fence(ck, tid >> 10);
#pragma unroll
      for (int q = 0; q < 6; q++) take(v[q]);
    }
    __nv_bfloat16* op = late.out + b0 + e;
    asm volatile("" : "+l"(op));
    if (last) named_bar_sync(10 + (e & 1), 160);
    take(lds128<3072>(ea));
    take(lds128<3072 + 512>(ea));
    asm volatile("" : "+f"(l), "+f"(a), "+r"(mx));
    sched_fence(ck, tid >> 10);
    asm volatile("{\n.reg .pred p, q;\nsetp.ne.u32 q, %1, 0;\nsetp.eq.and.u32 p|q, %0, 0, q;\n@p bar.sync 8, 160;\n@q bar.sync 9, 160;\n}"
                 ::"r"(e & 1), "r"((uint32_t)last) : "memory");
    {
      const uint4 v0 = lds128<4096>(ea + ck), v1 = lds128<4096 + 512>(ea);
      take(v0);
      take(v1);
    }
    const uint32_t big = __ballot_sync(0xffffffffu, ds <= fabsf(h_hi(mx)) * (1.f / 16384.f));
    const uint32_t bad = __ballot_sync(0xffffffffu, ((mx & 0x7fffu) > 0x7000u) | ((mx & 0x7c000000u) == 0x7c000000u));
    const bool ok = (big != 0u) & (bad == 0u) & ok_cta;
#pragma unroll
    for (int o = 0; o < 5; o++) {
      l += __uint_as_float(shfl_xor_v(__float_as_uint(l), 1 << o));
      a += __uint_as_float(shfl_xor_v(__float_as_uint(a), 1 << o));
    }
    float r;
    asm("rcp.approx.ftz.f32 %0, %1;" : "=f"(r) : "f"(l));
    if (lane == 0 && e < n_out) *op = __float2bfloat16_rn(a * 0.0625f * r);
    if (!ok && e < n_out)
      general_element(idx + (b0 + e) * kF, table, late.ii, late.jj, W, late.vec[0], late.vec[1], late.vec[2], op, reinterpret_cast<float*>(smem + OFF_EMB + e * kElem));
  }
}

__global__ void __launch_bounds__(kThreads, 1)
afm_kernel(const int* __restrict__ idx, const __nv_bfloat16* __restrict__ table, const __nv_bfloat16* __restrict__ W,
           uint32_t ix_stride, uint32_t ix_bias, uint32_t ix_last, int per, int n_elem, int n_left,
           const __grid_constant__ Late late) {
  extern __shared__ __align__(1024) uint8_t smem[];
  constexpr uint32_t sbase = 0x400u;

  const int tid = threadIdx.x;
  const int t = tid & 127;
  const int lane = tid & 31;
  const int warp = tid >> 5;
  uint32_t ck = 0;
  uint32_t never = tid >> 10;
  const int grp = 7 - (t >> 4);
  const bool v01 = grp < 7, v23 = grp < 6;
  const bool is_left = (int)blockIdx.x < n_left;
  const uint32_t ioff = blockIdx.x * ix_stride - ix_bias + ((tid >> 7) * kF + 4 * grp) * 4;
  uint2 gi01, gi23;
  ldg_idx4(gi01, gi23, idx, ioff <= ix_last ? ioff : 0u, v01 && tid < 256, v23 && tid < 256);
  asm volatile("{\n.reg .pred p;\nsetp.ge.u32 p, %1, %2;\n@p prefetch.global.L2 [%0];\n}" ::"l"(W + ((blockIdx.x * 32 + tid) & 255) * 64), "r"(tid), "n"(384 - 32) : "memory");
  sched_fence(ck, never);
  const int wq = warp & 3;
  const int wg = __shfl_sync(0xffffffffu, tid >> 7, 0);
  const int n_c = max(min(per, n_elem - ((int)blockIdx.x - n_left) * per), 2);
  const __nv_bfloat16* gsrc = table + (t & 15) * 8;
  asm volatile("" : "+l"(gsrc));
  uint32_t cv_ptr = sbase + OFF_EMB + wg * kElem + 4 * grp * kRow + (t & 15) * 16;

  if (wg < 2) {
    const int c = lane & 3;
    const int tau = t >> 2;
    if (wg == 0) {
      asm volatile("cp.async.ca.shared.global [%0], [%1], 4;\ncp.async.ca.shared.global [%0+4], [%2], 4;\ncp.async.commit_group;"
                   ::"r"(sbase + OFF_ES + t * 8), "l"(late.vec[t >> 6] + 2 * (t & 63)), "l"(late.vec[2] + 2 * (t & 63)) : "memory");
    }
    const int nb = (n_c - wg + 1) >> 1;
    const uint32_t sc = late.sched.e[tau];
    uint4 g0[4];
    const bool q01 = v01 && !is_left, q23 = v23 && !is_left;
    sched_fence(ck, never);
    if (wg == 1) {
      uint32_t y;
      asm volatile("or.b32 %0, %1, %2;" : "=r"(y) : "r"(gi01.x), "r"(gi23.x));
      const uint32_t t0 = clock32() + (y >> 31);
      while (clock32() - t0 < 450) {
      }
    }
    sched_fence(ck, never);
    g0[0] = ldg_row(gsrc, gi01.x, q01);
    g0[1] = ldg_row(gsrc, gi01.y, q01);
    g0[2] = ldg_row(gsrc, gi23.x, q23);
    g0[3] = ldg_row(gsrc, gi23.y, q23);
    sched_fence(ck, never);
    const int* lip = idx + min((int)(blockIdx.x * 256 + tau * 8 + wg), n_elem - 1) * kF;
    const uint2 li01 = ldg64p(lip, is_left), li23 = ldg64p(lip + 2, is_left);
    if (warp == 0) {
      if (lane == 0) {
#pragma unroll
        for (int i = 0; i < 16; i++) mbar_init(sbase + OFF_BAR + 8 * i, i < 2 ? 1 : i < 8 ? 4 : 128);
        mbar_arrive(sbase + OFF_BAR);
        mbar_arrive(sbase + OFF_BAR + 8);
      }
      if (smem_u32(smem) != sbase) __trap();
      __syncwarp();
      named_bar_arrive(6, 160);
    }
    if (wg == 0) {
      asm volatile("cp.async.wait_group 0;" ::: "memory");
      const uint32_t s0 = lds32(sbase + OFF_ES + t * 8), s1 = lds32(sbase + OFF_ES + t * 8 + 4);
      sts32(sbase + OFF_VEC + ((t & 112u) | ((t & 3u) << 2) | ((t >> 2) & 3u)) * 4,
            bf2h_x16(s0) ^ (t < 64 ? 0x80008000u : 0u));
      sts32(sbase + OFF_VEC + 512 + (t & 63) * 4, bf2h_x16(s1));
      named_bar_arrive(12, 256);
    }
    asm volatile("{\n.reg .pred p;\nsetp.eq.u32 p, %0, 0;\n@p bar.sync 1, 128;\n@!p bar.sync 12, 256;\n}" ::"r"(wg) : "memory");
    sched_fence(ck, never);
    uint32_t bs[16], hs[16], ps[16];
    load_vec(ps, sbase + OFF_VEC + 512 + c * 16);
    load_vec(bs, sbase + OFF_VEC + c * 16);
    load_vec(hs, sbase + OFF_VEC + 256 + c * 16);
    sched_fence(ck, never);
    if (wg == 1) named_bar_sync(7, 256);
    asm volatile("setmaxnreg.inc.sync.aligned.u32 %0;" ::"n"(216));
    if (wg == 0) named_bar_arrive(7, 256);
    uint32_t pt_ptr = shfl_xor<0>(sbase + OFF_ES + (2 + wg) * ES_STRIDE + t * 4);
    never = pt_ptr >> 31;
    uint32_t ra[6];
#pragma unroll
    for (int r = 0; r < 6; r++) ra[r] = sbase + OFF_EMB + wg * kElem + c * 16 + ((sc >> (5 * r)) & 31u) * kRow;
    asm volatile("" : "+r"(ra[0]), "+r"(ra[1]), "+r"(ra[2]), "+r"(ra[3]), "+r"(ra[4]), "+r"(ra[5]));
    sched_fence(ck, never);
    uint32_t Af[32], acc[32], S0[16], S1[16], S2[16], S3[16];
    constexpr uint64_t dB = (uint64_t)(((sbase + OFF_B) & 0x3FFFFu) >> 4) | ((uint64_t)(B_NBLK >> 4) << 16) |
                            ((uint64_t)(1024 >> 4) << 32) | ((uint64_t)1 << 62);
    auto products = [&](const uint32_t (&X)[16], const uint32_t (&Y)[16], const uint32_t (&Z)[16]) {
#pragma unroll
      for (int i = 0; i < 16; i++) {
        Af[2 * i] = hmul2(X[i], Z[i]);
        Af[2 * i + 1] = hmul2(Y[i], Z[i]);
      }
    };
    auto mma_tile = [&]() {
      fence_regs(Af);
      wgmma_fence();
#pragma unroll
      for (int s = 0; s < 8; s++) {
        const uint64_t d = dB + (uint64_t)(s * (2048 >> 4));
        if (s == 0) wgmma_rs_n128<0>(acc, Af[0], Af[1], Af[2], Af[3], d);
        else wgmma_rs_n128<1>(acc, Af[4 * s], Af[4 * s + 1], Af[4 * s + 2], Af[4 * s + 3], d);
      }
      wgmma_commit();
    };
    auto issue = [&]() {
      mma_tile();
      bar_arrive2<5, 4>(wg);
    };
    uint32_t eh0 = 0, eh1 = 0, sh0 = 0, sh1 = 0;
    auto fold = [&]() {
      eh0 = hadd2(__byte_perm(eh0, sh0, 0x5410), __byte_perm(eh0, sh0, 0x7632));
      eh1 = hadd2(__byte_perm(eh1, sh1, 0x5410), __byte_perm(eh1, sh1, 0x7632));
    };
    auto s_chain = [&]() {
      sh0 = hmul2(Af[0], ps[0]);
      sh1 = hmul2(Af[1], ps[0]);
#pragma unroll
      for (int i = 1; i < 16; i++) {
        sh0 = hfma2(Af[2 * i], ps[i], sh0);
        sh1 = hfma2(Af[2 * i + 1], ps[i], sh1);
      }
      asm volatile("" : "+r"(sh0), "+r"(sh1)::"memory");
    };
    auto epilogue = [&]() {
      wgmma_wait<0>();
      fence_regs(acc);
      fence_regs(S0); fence_regs(S1); fence_regs(S2); fence_regs(S3);
      eh0 = hmul2(bias_relu2(acc[0], bs[0]), hs[0]);
      eh1 = hmul2(bias_relu2(acc[1], bs[0]), hs[0]);
#pragma unroll
      for (int i = 1; i < 16; i++) {
        eh0 = hfma2(bias_relu2(acc[2 * i], bs[i]), hs[i], eh0);
        eh1 = hfma2(bias_relu2(acc[2 * i + 1], bs[i]), hs[i], eh1);
      }
      asm volatile("" : "+r"(eh0), "+r"(eh1)::"memory");
    };
    if (is_left) {
      if (wg == 1) named_bar_arrive(4, 256);
      const int e0 = shfl_xor<0>(blockIdx.x * 256 + tau * 8 + wg);
      const __nv_bfloat16* lsrc = table + c * 8;
      uint32_t ia, ib, ic, id, ma;
      float lsum = 0.f, asum = 0.f;
      auto load_ix = [&](int r) {
        const int* ip = idx + min(e0 + 2 * r, n_elem - 1) * kF;
        const uint2 x = ldg64(ip), y = ldg64(ip + 2);
        ia = x.x; ib = x.y; ic = y.x; id = y.y;
      };
      auto load_row = [&](uint32_t (&v)[16], uint32_t row) {
#pragma unroll
        for (int kb = 0; kb < 4; kb++) {
          const uint4 x = ldg_row(lsrc + 32 * kb, row, true);
          v[4 * kb] = x.x; v[4 * kb + 1] = x.y; v[4 * kb + 2] = x.z; v[4 * kb + 3] = x.w;
        }
      };
      auto cvt_row = [&](uint32_t (&v)[16]) {
#pragma unroll
        for (int i = 0; i < 16; i++) v[i] = bf2h(v[i]);
      };
      auto finish = [&](bool one_row) {
        s_chain();
        sched_fence(ck, never);
        epilogue();
        fold();
        uint32_t es = hadd2((c & 1) ? eh1 : eh0, shfl_xor<1>((c & 1) ? eh0 : eh1));
        es = hadd2(es, shfl_xor<2>(es));
        const float w = one_row && (c & 1) ? 0.f : exp_e(es);
        ma = habsmax2(ma, es);
        lsum += w;
        asum = fmaf(w, h_hi(es), asum);
        sched_fence(ck, never);
      };
      ia = li01.x; ib = li01.y; ic = li23.x; id = li23.y;
      load_row(S0, ia); load_row(S1, ib); load_row(S2, ic); load_row(S3, id);
      if (wg == 0) named_bar_sync(3, 256);
#pragma unroll 1
      for (int r = 0; r < 4; r++) {
        const int e = e0 + 2 * r;
        load_ix(r + 1);
        lsum = 0.f; asum = 0.f; ma = 0;
        cvt_row(S0); cvt_row(S1);
        products(S0, S0, S1);
        bar_sync2<4, 5>(wg);
        issue();
        cvt_row(S2); cvt_row(S3);
        finish(true);
        products(S0, S1, S2);
        bar_sync2<4, 5>(wg);
        issue();
        load_row(S2, ic);
        finish(false);
        products(S0, S1, S3);
        bar_sync2<4, 5>(wg);
        issue();
        load_row(S0, ia); load_row(S1, ib); load_row(S3, id);
        finish(false);
        lsum += __shfl_xor_sync(0xffffffffu, lsum, 1);
        asum += __shfl_xor_sync(0xffffffffu, asum, 1);
        ma = habsmax2(ma, shfl_xor<1>(ma));
        if ((ma & 0x7fffu) > 0x7000u || ((ma >> 16) & 0x7fffu) >= 0x7c00u) lsum = __int_as_float(0x7fffffff);
        if (c == 0 && e < n_elem)
          asm volatile("{\n.reg .b64 v;\nmov.b64 v, {%1,%2};\nst.volatile.global.b64 [%0], v;\n}" ::"l"(g_left + e + ck), "f"(lsum), "f"(asum) : "memory");
      }
      if (wg == 0) named_bar_sync(4, 256);
      return;
    }
    sts128p<0>(cv_ptr, convert_f(g0[0]), v01);
    sts128p<kRow>(cv_ptr, convert_f(g0[1]), v01);
    sts128p<2 * kRow>(cv_ptr, convert_f(g0[2]), v23);
    sts128p<3 * kRow>(cv_ptr, convert_f(g0[3]), v23);
    asm volatile("{\n.reg .pred p;\nsetp.eq.u32 p, %0, 0;\n@p bar.sync 3, 256;\n@!p bar.sync 2, 128;\n}" ::"r"(wg) : "memory");

    static_for<0, 4>([&](auto Kc) {
      constexpr int kb = decltype(Kc)::value;
      const uint4 z = lds128<64 * kb>(ra[5]), x = lds128<64 * kb>(ra[0]), y = lds128<64 * kb>(ra[1]);
      S3[4 * kb] = z.x; S3[4 * kb + 1] = z.y; S3[4 * kb + 2] = z.z; S3[4 * kb + 3] = z.w;
      S0[4 * kb] = x.x; S0[4 * kb + 1] = x.y; S0[4 * kb + 2] = x.z; S0[4 * kb + 3] = x.w;
      S1[4 * kb] = y.x; S1[4 * kb + 1] = y.y; S1[4 * kb + 2] = y.z; S1[4 * kb + 3] = y.w;
      if (kb & 1) sched_fence(ck, never);
    });
#pragma unroll
    for (int i = 0; i < 16; i++) S2[i] = 0;
    static_for<0, 2>([&](auto Hc) {
      constexpr int h = decltype(Hc)::value, n = 16 / 2;
#pragma unroll
      for (int i = h * n; i < h * n + n; i++) {
        Af[2 * i] = hmul2(S0[i], S3[i]);
        Af[2 * i + 1] = hmul2(S1[i], S3[i]);
        asm volatile("" : "+r"(Af[2 * i]), "+r"(Af[2 * i + 1])::"memory");
      }
      if (h == 0) {
        if (wg == 1) named_bar_sync(5, 256);
        sched_fence(ck, never);
      }
      wgmma_fence();
#pragma unroll
      for (int s = h * n / 2; s < (h * n + n) / 2; s++) {
        const uint64_t d = dB + (uint64_t)(s * (2048 >> 4));
        if (s == 0) wgmma_rs_n128<0>(acc, Af[0], Af[1], Af[2], Af[3], d);
        else wgmma_rs_n128<1>(acc, Af[4 * s], Af[4 * s + 1], Af[4 * s + 2], Af[4 * s + 3], d);
      }
      sched_fence(ck, never);
    });
    wgmma_commit();
    bar_arrive2<5, 4>(wg);
    sched_fence(ck, never);

    auto bump = [&](uint32_t& r) { asm volatile("add.u32 %0, %0, %1;" : "+r"(r) : "n"(2 * kElem)); };
    int left = nb - 1;
    ra[0] += 2 * kElem; ra[1] += 2 * kElem; ra[5] += 2 * kElem;
    uint4 r0, r1;
    uint32_t el = wg, rdy = 0;
    auto tile = [&](auto Tc) {
      constexpr int tt = decltype(Tc)::value & 7;
      constexpr bool last = decltype(Tc)::value > 7;
      sched_fence(ck, never);
      fold();
      const uint32_t f0 = eh0, f1 = eh1;
      sts32o<(tt == 0 ? 4096 - 2 * ES_STRIDE : (tt - 1) * 1024)>(pt_ptr, eh0);
      sts32o<(tt == 0 ? 4096 - 2 * ES_STRIDE : (tt - 1) * 1024) + 512>(pt_ptr, eh1);
      if (tt == 0) mbar_arrive(sbase + OFF_BAR + 64 + 8 * el);
      if (last) bar_arrive2<13, 14, 160>(wg);
      if (tt == 2) rdy = mbar_test(sbase + OFF_BAR + 8 * min(el + 2, n_c - 1), 0);
      sched_fence(ck, never);
      if (tt == 0) load_vec(S0, ra[3]);
      if (tt == 1) load_vec(S2, ra[4]);
      if (tt == 2) load_vec(S1, ra[2]);
      if (tt == 3 && !last) {
        load_vec(S0, ra[0]);
        r0 = lds128<0>(ra[1]);
        r1 = lds128<64>(ra[1]);
      }
      if (tt == 4) {
        load_vec(S3, ra[5]);
        const uint4 v2 = lds128<128>(ra[1]), v3 = lds128<192>(ra[1]);
        S1[8] = v2.x; S1[9] = v2.y; S1[10] = v2.z; S1[11] = v2.w; S1[12] = v3.x; S1[13] = v3.y; S1[14] = v3.z; S1[15] = v3.w;
        S1[0] = r0.x; S1[1] = r0.y; S1[2] = r0.z; S1[3] = r0.w; S1[4] = r1.x; S1[5] = r1.y; S1[6] = r1.z; S1[7] = r1.w;
      }
      sched_fence(ck, never);
      s_chain();
      sched_fence(ck, never);
      epilogue();
      sched_fence(ck, never);
      if (tt == 2 && !rdy) mbar_wait(sbase + OFF_BAR + 8 * min(el + 2, n_c - 1), 0);
      if (tt == 0) { products(S1, S3, S0); bump(ra[3]); }
      if (tt == 1) { products(S1, S0, S2); bump(ra[4]); }
      if (tt == 2) { products(S0, S2, S1); bump(ra[2]); }
      if (tt == 3) products(S1, S2, S3);
      if (tt == 4) {
        products(S0, S1, S3);
        bump(ra[0]); bump(ra[1]); bump(ra[5]);
        asm volatile("add.u32 %0, %0, %1;" : "+r"(pt_ptr) : "n"(2 * ES_STRIDE));
        el += 2;
      }
      sched_fence(ck, never);
      keep2(ck, f0, f1, never);
      bar_sync2<4, 5>(wg);
      issue();
    };
#pragma unroll 1
    for (;;) {
      tile(std::integral_constant<int, 0>{});
      tile(std::integral_constant<int, 1>{});
      tile(std::integral_constant<int, 2>{});
      if (left == 0) break;
      tile(std::integral_constant<int, 3>{});
      tile(std::integral_constant<int, 4>{});
      left--;
    }
    tile(std::integral_constant<int, 8 + 3>{});
    sched_fence(ck, never);
    fold();
    sts32o<3072>(pt_ptr, eh0);
    sts32o<3072 + 512>(pt_ptr, eh1);
    bar_arrive2<10, 11, 160>(wg);
    s_chain();
    sched_fence(ck, never);
    epilogue();
    sched_fence(ck, never);
    fold();
    sts32o<4096>(pt_ptr + ck, eh0);
    sts32o<4096 + 512>(pt_ptr, eh1);
    bar_arrive2<8, 9, 160>(wg);
    sched_fence(ck, never);
    if (wg == 0) {
      named_bar_sync(4, 256);
    } else if (n_c & 1) {
      for (int i = 0; i < 5; i++) {
        named_bar_sync(5, 256);
        named_bar_arrive(4, 256);
      }
    }
  } else {
    {
      asm volatile("setmaxnreg.dec.sync.aligned.u32 104;");
      uint4 wr[16];
#pragma unroll
      for (int r = 0; r < 16; r++) wr[r] = ldg128(W + (32 * wq + 2 * r) * kD + 8 * lane);
      const uint32_t wa = sbase + OFF_B + ((lane >> 3) & 1) * B_NBLK + wq * 4096 + (lane >> 4) * 128;
      const uint32_t lx = (lane & 7) ^ (lane >> 4);
      uint32_t wad[4], mw = 0;
#pragma unroll
      for (int x = 0; x < 4; x++) wad[x] = wa + ((lx ^ (2 * x)) << 4);
      sched_fence(ck, never);
      static_for<0, 16>([&](auto Rc) {
        constexpr int r = decltype(Rc)::value;
        uint4 v;
        v.x = bf2h_x16(wr[r].x); v.y = bf2h_x16(wr[r].y); v.z = bf2h_x16(wr[r].z); v.w = bf2h_x16(wr[r].w);
        sts128<(r & 3) * 1024 + (r >> 2) * 256>(wad[r >> 2], v);
        mw = babsmax2(babsmax2(mw, wr[r].x), babsmax2(wr[r].y, babsmax2(wr[r].z, wr[r].w)));
        if (r == 3) sched_fence(ck, never);
        if (r == 7 || r == 11) sched_fence(ck, never);
      });
      sched_fence(ck, never);
      fence_proxy_async();
      named_bar_arrive(3, 256);
      sched_fence(ck, never);
      sts32p(sbase + OFF_STAT + wq * 4 + ck, redux_max(absmax_bits(mw)), lane == 0);
    }
    asm volatile("setmaxnreg.dec.sync.aligned.u32 %0;" ::"n"(504 - 2 * 216));
    if ((int)blockIdx.x >= n_left) helper_rest(idx, table, W, late, per, n_elem, n_left, smem);
    else {
      named_bar_sync(6, 160);
#pragma unroll 1
      for (int q = 2; q < 8; q++) {
        const int e = min((int)blockIdx.x * 256 + (t >> 2) * 8 + q, n_elem - 1);
        const uint32_t row = ldg32(idx + e * kF + (t & 3));
        asm volatile("prefetch.global.L2 [%0];\nprefetch.global.L2 [%0+128];" ::"l"(table + (size_t)row * kD) : "memory");
      }
    }
  }
}

}

extern "C" void kernel_launch(void* const* d_in, const int* in_sizes, int n_in, void* d_out, int out_size) {
  const int* idx = (const int*)d_in[0];
  const __nv_bfloat16* table = (const __nv_bfloat16*)d_in[1];
  const int* ii = (const int*)d_in[2];
  const int* jj = (const int*)d_in[3];
  const __nv_bfloat16* W = (const __nv_bfloat16*)d_in[4];
  const __nv_bfloat16* bias = (const __nv_bfloat16*)d_in[5];
  const __nv_bfloat16* hvec = (const __nv_bfloat16*)d_in[6];
  const __nv_bfloat16* pvec = (const __nv_bfloat16*)d_in[7];
  __nv_bfloat16* out = (__nv_bfloat16*)d_out;
  const int B = out_size;

  static int num_sms = 0;
  if (num_sms == 0) {
    int dev = 0;
    cudaGetDevice(&dev);
    cudaDeviceGetAttribute(&num_sms, cudaDevAttrMultiProcessorCount, dev);
    cudaFuncSetAttribute(afm_kernel, cudaFuncAttributeMaxDynamicSharedMemorySize, SMEM_BYTES);
  }
  const Sched sched = {{
    0x2d2cb011u, 0x2c9a0662u, 0x2876c228u, 0x26074141u, 0x2655c878u, 0x2985dc43u, 0x18722403u, 0x22299aaeu,
    0x02a6b0b1u, 0x30d73d00u, 0x00941af1u, 0x2ee29c4au, 0x2ad5a410u, 0x21250923u, 0x328a84aeu, 0x0d780599u,
    0x324551f8u, 0x3112a583u, 0x062ca4eeu, 0x155360e3u, 0x1cb204d6u, 0x1f4280c9u, 0x2776e487u, 0x090b60a2u,
    0x2413bf17u, 0x168b28ecu, 0x10c78a70u, 0x2f578ed1u, 0x1a334ac2u, 0x0888c875u, 0x1d5a3249u, 0x2305bf2au
  }};
  for (int off = 0; off < B; off += kMaxChunk) {
    const int n = B - off < kMaxChunk ? B - off : kMaxChunk;
    const int n_left = (n + 255) / 256;
    const int room = num_sms - n_left > 1 ? num_sms - n_left : 1;
    int per = (n + room - 1) / room;
    if (per > kMaxB) per = kMaxB;
    const int n_main = (n + per - 1) / per;
    const Late late = {{bias, hvec, pvec, pvec}, ii, jj, out + off, sched};
    afm_kernel<<<n_left + n_main, kThreads, SMEM_BYTES>>>(idx + (size_t)off * kF, table, W, per * kF * 4, n_left * per * kF * 4,
                                                          (n * kF - 2) * 4, per, n, n_left, late);
  }
}
```

```cpp
#include <cuda_runtime.h>
#include <cuda_bf16.h>
#include <cuda_fp16.h>
#include <stdint.h>
#include <type_traits>

namespace {

constexpr int kF = 26;
constexpr int kD = 128;
constexpr int kP = 325;
constexpr int kMaxB = 8;
constexpr int kThreads = 384;
constexpr int kRow = 320;
constexpr int kElem = kF * kRow;

constexpr int B_NBLK = 16 * 1024;
constexpr int OFF_B = 0;
constexpr int OFF_EMB = 2 * B_NBLK;
constexpr int OFF_ES = OFF_EMB + kMaxB * kElem;
constexpr int ES_STRIDE = 5 * 1024;
constexpr int OFF_VEC = OFF_ES + (kMaxB + 2) * ES_STRIDE;
constexpr int OFF_STAT = OFF_VEC + 768;
constexpr int OFF_BAR = OFF_STAT + 128;
constexpr int SMEM_USED = OFF_BAR + 128;
static_assert(OFF_EMB + (kMaxB + 2) * kElem <= SMEM_USED, "unused operand prefetches run up to 2 elements past the end");
constexpr int SMEM_BYTES = SMEM_USED;
static_assert(OFF_ES % 16 == 0 && OFF_VEC % 16 == 0 && OFF_STAT % 16 == 0 && kElem % 128 == 0, "alignment");

struct Sched { uint32_t e[32]; };
struct Late {
  const __nv_bfloat16* vec[4];
  const int* ii;
  const int* jj;
  __nv_bfloat16* out;
  Sched sched;
};

constexpr int kMaxChunk = 8192;
__device__ float2 g_left[kMaxChunk];

__device__ __forceinline__ uint32_t smem_u32(const void* p) { return (uint32_t)__cvta_generic_to_shared(p); }
__device__ __forceinline__ void named_bar_sync(int id, int n) { asm volatile("bar.sync %0, %1;" ::"r"(id), "r"(n) : "memory"); }
__device__ __forceinline__ void named_bar_arrive(int id, int n) { asm volatile("bar.arrive %0, %1;" ::"r"(id), "r"(n) : "memory"); }
template <int A, int B>
__device__ __forceinline__ void bar_sync2(uint32_t sel) {
  asm volatile("{\n.reg .pred p;\nsetp.eq.u32 p, %0, 0;\n@p bar.sync %1, 256;\n@!p bar.sync %2, 256;\n}" ::"r"(sel), "n"(A), "n"(B) : "memory");
}
template <int A, int B, int N = 256>
__device__ __forceinline__ void bar_arrive2(uint32_t sel) {
  asm volatile("{\n.reg .pred p;\nsetp.eq.u32 p, %0, 0;\n@p bar.arrive %1, %3;\n@!p bar.arrive %2, %3;\n}" ::"r"(sel), "n"(A), "n"(B), "n"(N) : "memory");
}
__device__ __forceinline__ void mbar_init(uint32_t bar, uint32_t count) {
  asm volatile("mbarrier.init.shared::cta.b64 [%0], %1;" ::"r"(bar), "r"(count) : "memory");
}
__device__ __forceinline__ void mbar_arrive(uint32_t bar) {
  asm volatile("mbarrier.arrive.shared::cta.b64 _, [%0];" ::"r"(bar) : "memory");
}
__device__ __forceinline__ void mbar_arrive_p(uint32_t bar, bool on) {
  asm volatile("{\n.reg .pred p;\nsetp.ne.u32 p, %1, 0;\n@p mbarrier.arrive.shared::cta.b64 _, [%0];\n}" ::"r"(bar), "r"((uint32_t)on) : "memory");
}
__device__ __forceinline__ uint32_t mbar_test(uint32_t bar, uint32_t parity) {
  uint32_t ok;
  asm volatile("{\n.reg .pred p;\nmbarrier.test_wait.parity.shared::cta.b64 p, [%1], %2;\nselp.u32 %0, 1, 0, p;\n}\n"
               : "=r"(ok) : "r"(bar), "r"(parity) : "memory");
  return ok;
}
__device__ __forceinline__ void mbar_wait(uint32_t bar, uint32_t parity) {
  uint32_t ok, it = 0;
  do {
    asm volatile("{\n.reg .pred p;\nmbarrier.try_wait.parity.shared::cta.b64 p, [%1], %2, %3;\nselp.u32 %0, 1, 0, p;\n}\n"
                 : "=r"(ok) : "r"(bar), "r"(parity), "r"(20000) : "memory");
  } while (!ok && ++it < (1u << 16));
}
__device__ __forceinline__ void wgmma_fence() { asm volatile("wgmma.fence.sync.aligned;" ::: "memory"); }
__device__ __forceinline__ void wgmma_commit() { asm volatile("wgmma.commit_group.sync.aligned;" ::: "memory"); }
template <int N>
__device__ __forceinline__ void wgmma_wait() { asm volatile("wgmma.wait_group.sync.aligned %0;" ::"n"(N) : "memory"); }
__device__ __forceinline__ void fence_proxy_async() { asm volatile("fence.proxy.async.shared::cta;" ::: "memory"); }

__device__ __forceinline__ uint32_t hmul2(uint32_t a, uint32_t b) {
  uint32_t d;
  asm("mul.rn.f16x2 %0, %1, %2;" : "=r"(d) : "r"(a), "r"(b));
  return d;
}
__device__ __forceinline__ uint32_t hadd2(uint32_t a, uint32_t b) {
  uint32_t d;
  asm("add.rn.f16x2 %0, %1, %2;" : "=r"(d) : "r"(a), "r"(b));
  return d;
}
__device__ __forceinline__ uint32_t hfma2(uint32_t a, uint32_t b, uint32_t c) {
  uint32_t d;
  asm("fma.rn.f16x2 %0, %1, %2, %3;" : "=r"(d) : "r"(a), "r"(b), "r"(c));
  return d;
}
__device__ __forceinline__ uint32_t bias_relu2(uint32_t x, uint32_t nb) {
  uint32_t d;
  asm("max.NaN.f16x2 %0, %1, %2;" : "=r"(d) : "r"(x), "r"(nb));
  return d;
}
__device__ __forceinline__ uint32_t habsmax2(uint32_t a, uint32_t b) {
  uint32_t d;
  asm("max.NaN.xorsign.abs.f16x2 %0, %1, %2;" : "=r"(d) : "r"(a), "r"(b));
  return d;
}
__device__ __forceinline__ uint32_t babsmax2(uint32_t a, uint32_t b) {
  uint32_t d;
  asm("max.NaN.xorsign.abs.bf16x2 %0, %1, %2;" : "=r"(d) : "r"(a), "r"(b));
  return d;
}
__device__ __forceinline__ uint32_t bf2h(uint32_t x) {
  uint32_t d;
  asm("cvt.rn.f16x2.f32 %0, %1, %2;" : "=r"(d) : "f"(__uint_as_float(x & 0xffff0000u)), "f"(__uint_as_float(x << 16)));
  return d;
}
__device__ __forceinline__ uint32_t bf2h_x16(uint32_t x) {
  uint32_t hi, lo, d;
  asm("fma.rn.bf16x2 %0, %1, %2, %3;" : "=r"(hi) : "r"(x), "r"(0x41800000u), "r"(0u));
  asm("{\n.reg .b16 l, h;\n.reg .b32 t;\nmov.b32 {l, h}, %1;\nmov.b32 t, {l, l};\nfma.rn.bf16x2 %0, t, %2, %3;\n}"
      : "=r"(lo) : "r"(x), "r"(0x41800000u), "r"(0u));
  asm("cvt.rn.f16x2.f32 %0, %1, %2;" : "=r"(d) : "f"(__uint_as_float(hi)), "f"(__uint_as_float(lo)));
  return d;
}
template <bool HI_FMA>
__device__ __forceinline__ uint32_t bf2h_f(uint32_t x) {
  uint32_t hi = x & 0xffff0000u, lo, d;
  if (HI_FMA) asm("fma.rn.bf16x2 %0, %1, %2, %3;" : "=r"(hi) : "r"(x), "r"(0x3f800000u), "r"(0u));
  asm("{\n.reg .b16 l, h;\n.reg .b32 t;\nmov.b32 {l, h}, %1;\nmov.b32 t, {l, l};\nfma.rn.bf16x2 %0, t, %2, %3;\n}"
      : "=r"(lo) : "r"(x), "r"(0x3f800000u), "r"(0u));
  asm("cvt.rn.f16x2.f32 %0, %1, %2;" : "=r"(d) : "f"(__uint_as_float(hi)), "f"(__uint_as_float(lo)));
  return d;
}
__device__ __forceinline__ uint4 convert(uint4 v) { return make_uint4(bf2h(v.x), bf2h(v.y), bf2h(v.z), bf2h(v.w)); }
__device__ __forceinline__ uint4 convert_f(uint4 v) {
  return make_uint4(bf2h_f<false>(v.x), bf2h_f<true>(v.y), bf2h_f<false>(v.z), bf2h_f<true>(v.w));
}
__device__ __forceinline__ float h_lo(uint32_t x) { return __half2float(__ushort_as_half((unsigned short)(x & 0xffffu))); }
__device__ __forceinline__ float h_hi(uint32_t x) { return __half2float(__ushort_as_half((unsigned short)(x >> 16))); }
__device__ __forceinline__ uint32_t redux_max(uint32_t v) {
  uint32_t d;
  asm volatile("redux.sync.max.u32 %0, %1, 0xffffffff;" : "=r"(d) : "r"(v));
  return d;
}
__device__ __forceinline__ uint32_t absmax_bits(uint32_t m) { return max(m & 0x7fffu, (m >> 16) & 0x7fffu); }

template <int OFF>
__device__ __forceinline__ uint4 lds128(uint32_t addr) {
  uint4 v;
  asm volatile("ld.shared.v4.u32 {%0,%1,%2,%3}, [%4+%5];" : "=r"(v.x), "=r"(v.y), "=r"(v.z), "=r"(v.w) : "r"(addr), "n"(OFF));
  return v;
}
template <int OFF>
__device__ __forceinline__ void sts128(uint32_t addr, uint4 v) {
  asm volatile("st.shared.v4.u32 [%0+%5], {%1,%2,%3,%4};" ::"r"(addr), "r"(v.x), "r"(v.y), "r"(v.z), "r"(v.w), "n"(OFF) : "memory");
}
__device__ __forceinline__ uint32_t lds32(uint32_t addr) {
  uint32_t v;
  asm volatile("ld.shared.u32 %0, [%1];" : "=r"(v) : "r"(addr));
  return v;
}
__device__ __forceinline__ void sts32(uint32_t addr, uint32_t v) { asm volatile("st.shared.u32 [%0], %1;" ::"r"(addr), "r"(v) : "memory"); }
__device__ __forceinline__ uint32_t ldg32(const void* p) {
  uint32_t v;
  asm volatile("ld.global.u32 %0, [%1];" : "=r"(v) : "l"(p) : "memory");
  return v;
}
__device__ __forceinline__ uint4 ldg128(const void* p) {
  uint4 v;
  asm volatile("ld.global.v4.u32 {%0,%1,%2,%3}, [%4];" : "=r"(v.x), "=r"(v.y), "=r"(v.z), "=r"(v.w) : "l"(p) : "memory");
  return v;
}
__device__ __forceinline__ uint2 ldg64(const void* p) {
  uint2 v;
  asm volatile("ld.global.v2.u32 {%0,%1}, [%2];" : "=r"(v.x), "=r"(v.y) : "l"(p) : "memory");
  return v;
}
__device__ __forceinline__ uint2 ldg64p(const void* p, bool on) {
  uint2 v;
  asm volatile("{\n.reg .pred p;\nsetp.ne.u32 p, %3, 0;\n@p ld.volatile.global.v2.u32 {%0,%1}, [%2];\n}" : "=r"(v.x), "=r"(v.y) : "l"(p), "r"((uint32_t)on) : "memory");
  return v;
}
__device__ __forceinline__ void ldg_idx4(uint2& x, uint2& y, const void* base, uint32_t off, bool on0, bool on1) {
  asm volatile("{\n.reg .pred p, q;\n.reg .b64 a;\n.reg .b32 lo, hi;\nsetp.ne.u32 p, %6, 0;\nsetp.ne.u32 q, %7, 0;\n"
               "mov.b64 {lo, hi}, %4;\nadd.cc.u32 lo, lo, %5;\naddc.u32 hi, hi, 0;\nmov.b64 a, {lo, hi};\n"
               "@p ld.volatile.global.v2.u32 {%0,%1}, [a];\n@q ld.volatile.global.v2.u32 {%2,%3}, [a+8];\n}"
               : "=r"(x.x), "=r"(x.y), "=r"(y.x), "=r"(y.y) : "l"(base), "r"(off), "r"((uint32_t)on0), "r"((uint32_t)on1) : "memory");
}
__device__ __forceinline__ uint4 ldg_row(const void* base, uint32_t row, bool on) {
  uint4 v;
  asm volatile("{\n.reg .pred p;\n.reg .b64 a;\nsetp.ne.u32 p, %6, 0;\nmad.wide.u32 a, %5, 256, %4;\n@p ld.global.v4.u32 {%0,%1,%2,%3}, [a];\n}"
               : "=r"(v.x), "=r"(v.y), "=r"(v.z), "=r"(v.w) : "l"(base), "r"(row), "r"((uint32_t)on) : "memory");
  return v;
}
template <int OFF>
__device__ __forceinline__ void sts128p(uint32_t addr, uint4 v, bool on) {
  asm volatile("{\n.reg .pred p;\nsetp.ne.u32 p, %6, 0;\n@p st.shared.v4.u32 [%0+%5], {%1,%2,%3,%4};\n}"
               ::"r"(addr), "r"(v.x), "r"(v.y), "r"(v.z), "r"(v.w), "n"(OFF), "r"((uint32_t)on) : "memory");
}
__device__ __forceinline__ void sts32p(uint32_t addr, uint32_t v, bool on) {
  asm volatile("{\n.reg .pred p;\nsetp.ne.u32 p, %2, 0;\n@p st.shared.u32 [%0], %1;\n}" ::"r"(addr), "r"(v), "r"((uint32_t)on) : "memory");
}
__device__ __forceinline__ uint32_t shfl_xor_v(uint32_t v, int m) {
  uint32_t d;
  asm volatile("shfl.sync.bfly.b32 %0, %1, %2, 0x1f, 0xffffffff;" : "=r"(d) : "r"(v), "r"(m));
  return d;
}
template <int M>
__device__ __forceinline__ uint32_t shfl_xor(uint32_t v) {
  uint32_t d;
  asm volatile("shfl.sync.bfly.b32 %0, %1, %2, 0x1f, 0xffffffff;" : "=r"(d) : "r"(v), "n"(M));
  return d;
}
template <int I, int N, typename F>
__device__ __forceinline__ void static_for(F&& f) {
  if constexpr (I < N) {
    f(std::integral_constant<int, I>{});
    static_for<I + 1, N>(f);
  }
}
template <int N>
__device__ __forceinline__ void fence_regs(uint32_t (&r)[N]) {
#pragma unroll
  for (int i = 0; i < N; i++) asm volatile("" : "+r"(r[i])::"memory");
}
__device__ __forceinline__ void load_vec(uint32_t (&v)[16], uint32_t a) {
  const uint4 v0 = lds128<0>(a), v1 = lds128<64>(a), v2 = lds128<128>(a), v3 = lds128<192>(a);
  v[0] = v0.x; v[1] = v0.y; v[2] = v0.z; v[3] = v0.w; v[4] = v1.x; v[5] = v1.y; v[6] = v1.z; v[7] = v1.w;
  v[8] = v2.x; v[9] = v2.y; v[10] = v2.z; v[11] = v2.w; v[12] = v3.x; v[13] = v3.y; v[14] = v3.z; v[15] = v3.w;
}

template <int OFF>
__device__ __forceinline__ void sts32o(uint32_t addr, uint32_t v) {
  asm volatile("st.shared.u32 [%0+%2], %1;" ::"r"(addr), "r"(v), "n"(OFF) : "memory");
}
__device__ __forceinline__ void keep2(uint32_t& ck, uint32_t a, uint32_t b, uint32_t never) {
  asm volatile("{\n.reg .pred p;\nsetp.ne.u32 p, %3, 0;\n@p xor.b32 %0, %1, %2;\n}" : "+r"(ck) : "r"(a), "r"(b), "r"(never));
}
__device__ __forceinline__ float exp_e(uint32_t es) {
  float w;
  asm("ex2.approx.ftz.f32 %0, %1;" : "=f"(w) : "f"(h_lo(es) * (1.4426950408889634f / 256.f)));
  return w;
}
__device__ __forceinline__ uint32_t clock32() {
  uint32_t v;
  asm volatile("mov.u32 %0, %%clock;" : "=r"(v)::"memory");
  return v;
}
__device__ __forceinline__ void sched_fence(uint32_t& ck, uint32_t never) {
  asm volatile("{\n.reg .pred p;\nsetp.ne.u32 p, %1, 0;\n@p mov.u32 %0, %%clock;\n}" : "+r"(ck) : "r"(never) : "memory");
}

template <int ACCUM>
__device__ __forceinline__ void wgmma_rs_n128(uint32_t (&d)[32], uint32_t a0, uint32_t a1, uint32_t a2, uint32_t a3, uint64_t descB) {
  if (ACCUM == 1) {
    asm volatile(
        "wgmma.mma_async.sync.aligned.m64n128k16.f16.f16.f16 "
        "{%0, %1, %2, %3, %4, %5, %6, %7, %8, %9, %10, %11, %12, %13, %14, %15, %16, %17, %18, %19, %20, %21, %22, %23, %24, %25, %26, %27, %28, %29, %30, %31}, "
        "{%32, %33, %34, %35}, %36, 1, 1, 1, 1;\n"
        : "+r"(d[0]), "+r"(d[1]), "+r"(d[2]), "+r"(d[3]), "+r"(d[4]), "+r"(d[5]), "+r"(d[6]), "+r"(d[7]), "+r"(d[8]), "+r"(d[9]), "+r"(d[10]), "+r"(d[11]), "+r"(d[12]), "+r"(d[13]), "+r"(d[14]), "+r"(d[15]), "+r"(d[16]), "+r"(d[17]), "+r"(d[18]), "+r"(d[19]), "+r"(d[20]), "+r"(d[21]), "+r"(d[22]), "+r"(d[23]), "+r"(d[24]), "+r"(d[25]), "+r"(d[26]), "+r"(d[27]), "+r"(d[28]), "+r"(d[29]), "+r"(d[30]), "+r"(d[31])
        : "r"(a0), "r"(a1), "r"(a2), "r"(a3), "l"(descB));
  }
  if (ACCUM == 0) {
    asm volatile(
        "wgmma.mma_async.sync.aligned.m64n128k16.f16.f16.f16 "
        "{%0, %1, %2, %3, %4, %5, %6, %7, %8, %9, %10, %11, %12, %13, %14, %15, %16, %17, %18, %19, %20, %21, %22, %23, %24, %25, %26, %27, %28, %29, %30, %31}, "
        "{%32, %33, %34, %35}, %36, 0, 1, 1, 1;\n"
        : "=r"(d[0]), "=r"(d[1]), "=r"(d[2]), "=r"(d[3]), "=r"(d[4]), "=r"(d[5]), "=r"(d[6]), "=r"(d[7]), "=r"(d[8]), "=r"(d[9]), "=r"(d[10]), "=r"(d[11]), "=r"(d[12]), "=r"(d[13]), "=r"(d[14]), "=r"(d[15]), "=r"(d[16]), "=r"(d[17]), "=r"(d[18]), "=r"(d[19]), "=r"(d[20]), "=r"(d[21]), "=r"(d[22]), "=r"(d[23]), "=r"(d[24]), "=r"(d[25]), "=r"(d[26]), "=r"(d[27]), "=r"(d[28]), "=r"(d[29]), "=r"(d[30]), "=r"(d[31])
        : "r"(a0), "r"(a1), "r"(a2), "r"(a3), "l"(descB));
  }
}
template <int ACCUM>
__device__ __forceinline__ void wgmma_rs_n96(uint32_t (&d)[24], uint32_t a0, uint32_t a1, uint32_t a2, uint32_t a3, uint64_t descB) {
  if (ACCUM == 1) {
    asm volatile(
        "wgmma.mma_async.sync.aligned.m64n96k16.f16.f16.f16 "
        "{%0, %1, %2, %3, %4, %5, %6, %7, %8, %9, %10, %11, %12, %13, %14, %15, %16, %17, %18, %19, %20, %21, %22, %23}, "
        "{%24, %25, %26, %27}, %28, 1, 1, 1, 1;\n"
        : "+r"(d[0]), "+r"(d[1]), "+r"(d[2]), "+r"(d[3]), "+r"(d[4]), "+r"(d[5]), "+r"(d[6]), "+r"(d[7]), "+r"(d[8]), "+r"(d[9]), "+r"(d[10]), "+r"(d[11]), "+r"(d[12]), "+r"(d[13]), "+r"(d[14]), "+r"(d[15]), "+r"(d[16]), "+r"(d[17]), "+r"(d[18]), "+r"(d[19]), "+r"(d[20]), "+r"(d[21]), "+r"(d[22]), "+r"(d[23])
        : "r"(a0), "r"(a1), "r"(a2), "r"(a3), "l"(descB));
  }
  if (ACCUM == 0) {
    asm volatile(
        "wgmma.mma_async.sync.aligned.m64n96k16.f16.f16.f16 "
        "{%0, %1, %2, %3, %4, %5, %6, %7, %8, %9, %10, %11, %12, %13, %14, %15, %16, %17, %18, %19, %20, %21, %22, %23}, "
        "{%24, %25, %26, %27}, %28, 0, 1, 1, 1;\n"
        : "=r"(d[0]), "=r"(d[1]), "=r"(d[2]), "=r"(d[3]), "=r"(d[4]), "=r"(d[5]), "=r"(d[6]), "=r"(d[7]), "=r"(d[8]), "=r"(d[9]), "=r"(d[10]), "=r"(d[11]), "=r"(d[12]), "=r"(d[13]), "=r"(d[14]), "=r"(d[15]), "=r"(d[16]), "=r"(d[17]), "=r"(d[18]), "=r"(d[19]), "=r"(d[20]), "=r"(d[21]), "=r"(d[22]), "=r"(d[23])
        : "r"(a0), "r"(a1), "r"(a2), "r"(a3), "l"(descB));
  }
}
template <int ACCUM>
__device__ __forceinline__ void wgmma_rs_n32(uint32_t (&d)[8], uint32_t a0, uint32_t a1, uint32_t a2, uint32_t a3, uint64_t descB) {
  if (ACCUM == 1) {
    asm volatile(
        "wgmma.mma_async.sync.aligned.m64n32k16.f16.f16.f16 "
        "{%0, %1, %2, %3, %4, %5, %6, %7}, "
        "{%8, %9, %10, %11}, %12, 1, 1, 1, 1;\n"
        : "+r"(d[0]), "+r"(d[1]), "+r"(d[2]), "+r"(d[3]), "+r"(d[4]), "+r"(d[5]), "+r"(d[6]), "+r"(d[7])
        : "r"(a0), "r"(a1), "r"(a2), "r"(a3), "l"(descB));
  }
  if (ACCUM == 0) {
    asm volatile(
        "wgmma.mma_async.sync.aligned.m64n32k16.f16.f16.f16 "
        "{%0, %1, %2, %3, %4, %5, %6, %7}, "
        "{%8, %9, %10, %11}, %12, 0, 1, 1, 1;\n"
        : "=r"(d[0]), "=r"(d[1]), "=r"(d[2]), "=r"(d[3]), "=r"(d[4]), "=r"(d[5]), "=r"(d[6]), "=r"(d[7])
        : "r"(a0), "r"(a1), "r"(a2), "r"(a3), "l"(descB));
  }
}

__device__ __forceinline__ float rbf(float x) { return __bfloat162float(__float2bfloat16_rn(x)); }
__device__ __forceinline__ float warp_sum(float v) {
#pragma unroll
  for (int o = 16; o > 0; o >>= 1) v += __shfl_xor_sync(0xffffffffu, v, o);
  return v;
}

__device__ __noinline__ void general_element(const int* __restrict__ idx, const __nv_bfloat16* __restrict__ table,
                                             const int* __restrict__ ii, const int* __restrict__ jj,
                                             const __nv_bfloat16* __restrict__ W, const __nv_bfloat16* __restrict__ bias,
                                             const __nv_bfloat16* __restrict__ hvec, const __nv_bfloat16* __restrict__ pvec,
                                             __nv_bfloat16* __restrict__ out, float* ev) {
  const int lane = threadIdx.x & 31;
  auto pair4 = [&](int p, float (&pr)[4]) {
    const __nv_bfloat16* a = table + (size_t)idx[ii[p]] * kD + 4 * lane;
    const __nv_bfloat16* b = table + (size_t)idx[jj[p]] * kD + 4 * lane;
#pragma unroll
    for (int q = 0; q < 4; q++) pr[q] = rbf(__bfloat162float(a[q]) * __bfloat162float(b[q]));
  };
  float m = -INFINITY;
  bool has_nan = false;
  for (int p = 0; p < kP; p++) {
    float pr[4], x[4] = {0.f, 0.f, 0.f, 0.f};
    pair4(p, pr);
    for (int l = 0; l < 32; l++) {
#pragma unroll
      for (int q = 0; q < 4; q++) {
        const float v = __shfl_sync(0xffffffffu, pr[q], l);
        const uint2 w = *reinterpret_cast<const uint2*>(W + (4 * l + q) * kD + 4 * lane);
        x[0] = fmaf(v, __uint_as_float(w.x << 16), x[0]);
        x[1] = fmaf(v, __uint_as_float(w.x & 0xffff0000u), x[1]);
        x[2] = fmaf(v, __uint_as_float(w.y << 16), x[2]);
        x[3] = fmaf(v, __uint_as_float(w.y & 0xffff0000u), x[3]);
      }
    }
    float e = 0.f;
#pragma unroll
    for (int q = 0; q < 4; q++) {
      const float y = rbf(rbf(x[q]) + __bfloat162float(bias[4 * lane + q]));
      e = fmaf(rbf(0.5f * rbf(y + fabsf(y))), __bfloat162float(hvec[4 * lane + q]), e);
    }
    e = rbf(warp_sum(e));
    has_nan |= (e != e);
    m = fmaxf(m, e);
    if (lane == 0) ev[p] = e;
  }
  __syncwarp();
  float l = 0.f;
  for (int p = lane; p < kP; p += 32) l += expf(ev[p] - m);
  l = warp_sum(l);
  float pooled[4] = {0.f, 0.f, 0.f, 0.f};
  for (int p = 0; p < kP; p++) {
    float pr[4];
    pair4(p, pr);
    const float al = rbf(expf(ev[p] - m) / l);
#pragma unroll
    for (int q = 0; q < 4; q++) pooled[q] = fmaf(al, pr[q], pooled[q]);
  }
  float o = 0.f;
#pragma unroll
  for (int q = 0; q < 4; q++) o = fmaf(rbf(pooled[q]), __bfloat162float(pvec[4 * lane + q]), o);
  o = warp_sum(o);
  if (has_nan) o = __int_as_float(0x7fffffff);
  if (lane == 0) *out = __float2bfloat16_rn(o);
}

__device__ __forceinline__ void helper_rest(const int* __restrict__ idx, const __nv_bfloat16* __restrict__ table,
                                            const __nv_bfloat16* __restrict__ W, const Late& late, int per, int n_elem,
                                            int n_left, uint8_t* smem) {
  constexpr uint32_t sbase = 0x400u;
  uint32_t tid, cta;
  asm volatile("mov.u32 %0, %%tid.x;\nmov.u32 %1, %%ctaid.x;" : "=r"(tid), "=r"(cta));
  const int t = tid & 127, lane = tid & 31, wq = (tid >> 5) & 3;
  cta -= n_left;
  const int b0 = cta * per, last_row = n_elem * kF - 2;
  const int n_out = min(per, n_elem - b0), n_c = max(n_out, 2);
  const int grp = 7 - (t >> 4);
  const bool v01 = grp < 7, v23 = grp < 6;
  int irow = (b0 + (n_c > 2 ? 2 : 0)) * kF + 4 * grp;
  uint2 gi01 = ldg64(idx + min(irow, last_row));
  uint2 gi23 = ldg64(idx + min(irow + 2, last_row));
  const __nv_bfloat16* gsrc = table + (t & 15) * 8;
  uint32_t cv_ptr = sbase + OFF_EMB + 2 * kElem + 4 * grp * kRow + (t & 15) * 16;
  uint32_t me = 0, ck = 0;
  auto track = [&](const uint4& a, const uint4& b, bool on) {
    const uint32_t m = babsmax2(babsmax2(babsmax2(a.x, a.y), babsmax2(a.z, a.w)), babsmax2(babsmax2(b.x, b.y), babsmax2(b.z, b.w)));
    me = babsmax2(me, on ? m : 0u);
  };
  named_bar_sync(6, 160);
#pragma unroll 1
  for (int e = 2; e < n_c + 2; e++) {
    const uint4 g0 = ldg_row(gsrc, gi01.x, v01), g1 = ldg_row(gsrc, gi01.y, v01);
    const uint4 g2 = ldg_row(gsrc, gi23.x, v23), g3 = ldg_row(gsrc, gi23.y, v23);
    irow += e + 1 == n_c ? (1 - n_c) * kF : kF;
    gi01 = ldg64(idx + min(irow, last_row));
    gi23 = ldg64(idx + min(irow + 2, last_row));
    uint4 h0 = convert(g0), h1 = convert(g1), h2 = convert(g2), h3 = convert(g3);
    asm volatile("" : "+r"(h0.x), "+r"(h0.y), "+r"(h0.z), "+r"(h0.w), "+r"(h1.x), "+r"(h1.y), "+r"(h1.z), "+r"(h1.w),
                      "+r"(h2.x), "+r"(h2.y), "+r"(h2.z), "+r"(h2.w), "+r"(h3.x), "+r"(h3.y), "+r"(h3.z), "+r"(h3.w));
    sched_fence(ck, tid >> 10);
    sts128p<0>(cv_ptr, h0, v01 && e < n_c);
    sts128p<kRow>(cv_ptr, h1, v01 && e < n_c);
    sts128p<2 * kRow>(cv_ptr, h2, v23 && e < n_c);
    sts128p<3 * kRow>(cv_ptr, h3, v23 && e < n_c);
    __syncwarp();
    mbar_arrive_p(sbase + OFF_BAR + 8 * e, lane == 0 && e < n_c);
    sched_fence(ck, tid >> 10);
    cv_ptr += kElem;
    track(g0, g1, v01);
    track(g2, g3, v23);
  }
  bool ok_cta;
  float ds;
  {
    const uint32_t s0 = ldg32(late.vec[t >> 6] + 2 * (t & 63)), s1 = ldg32(late.vec[2] + 2 * (t & 63));
    const uint32_t s2 = ldg32(late.vec[(t >> 6) ^ 1] + 2 * (t & 63));
    uint32_t pi[3], pj[3];
#pragma unroll
    for (int r = 0; r < 3; r++) {
      pi[r] = ldg32(late.ii + min(t + 128 * r, kP - 1));
      pj[r] = ldg32(late.jj + min(t + 128 * r, kP - 1));
    }
    float v0 = 16.f * (fabsf(__uint_as_float(s0 << 16)) + fabsf(__uint_as_float(s0 & 0xffff0000u)));
    float v1 = 16.f * (fabsf(__uint_as_float(s1 << 16)) + fabsf(__uint_as_float(s1 & 0xffff0000u)));
    if (t >= 64) v1 = fabsf(__uint_as_float(s0 << 16) * __uint_as_float(s2 << 16)) +
                      fabsf(__uint_as_float(s0 & 0xffff0000u) * __uint_as_float(s2 & 0xffff0000u));
    bool good = true;
#pragma unroll
    for (int r = 0; r < 3; r++)
      good &= (pi[r] < pj[r]) & (pj[r] < kF) & (((pi[r] * (2 * kF - 1 - pi[r])) >> 1) + pj[r] - pi[r] - 1 == min(t + 128 * r, kP - 1));
    if (!good) v0 = __int_as_float(0x7fffffff);
    v0 = warp_sum(v0);
    v1 = warp_sum(v1);
    sts32p(sbase + OFF_STAT + 64 + wq * 4, __float_as_uint(v0), lane == 0);
    sts32p(sbase + OFF_STAT + 80 + wq * 4, __float_as_uint(v1), lane == 0);
    sts32p(sbase + OFF_STAT + 16 + wq * 4 + ck, redux_max(absmax_bits(me)), lane == 0);
    named_bar_sync(6, 128);
    const uint32_t st = lds32(sbase + OFF_STAT + lane * 4);
    const float Wm = 2048.f * __uint_as_float(redux_max(lane < 4 ? st : 0u) << 16);
    const float M = __uint_as_float(redux_max(lane >= 4 && lane < 8 ? st : 0u) << 16);
    const float sp = __uint_as_float(st) + __shfl_xor_sync(0xffffffffu, __uint_as_float(st), 1);
    const float Bs = __shfl_sync(0xffffffffu, sp, 16);
    const float Hs = __shfl_sync(0xffffffffu, sp, 18);
    const float Ps = __shfl_sync(0xffffffffu, sp, 20);
    const float HB = __shfl_sync(0xffffffffu, sp, 22);
    const float M2 = M * M, X = fmaf(M2, Wm, Bs), G = fmaf(2.f, M, 1.f);
    constexpr float u = 1.f / 33554432.f;
    const float de = u * (Hs * (Wm * G + 128.f * M2 + 16.f) + 128.f * X + 256.f);
    ds = u * (Ps * G + 128.f * M2 + 256.f);
    ok_cta = M2 <= 60000.f && Wm <= 128.f * 60000.f && X <= 60000.f && Hs <= 60000.f && Ps <= 60000.f && de <= 1.f && HB <= 64.f;
  }
#pragma unroll 1
  for (int e = wq; e < n_c; e += 4) {
    const uint32_t ea = sbase + OFF_ES + (2 + e) * ES_STRIDE + lane * 16;
    float l = 0.f, a = 0.f;
    if (lane == 0 && e < n_out) {
      float2* const gp = g_left + b0 + e;
      for (uint32_t it = 0; it < (1u << 22); it++) {
        asm volatile("{\n.reg .b64 v;\nld.volatile.global.b64 v, [%2];\nmov.b64 {%0,%1}, v;\n}" : "=f"(l), "=f"(a) : "l"(gp) : "memory");
        if (__float_as_uint(l) != 0u) break;
        __nanosleep(200);
      }
      asm volatile("st.volatile.global.b64 [%0], %1;" ::"l"(gp), "l"(0ull) : "memory");
    }
    __syncwarp();
    uint32_t mx = lane == 0 && !(l > 0.f) ? 0x7fffu : 0u;
    auto take = [&](const uint4& v) {
      const uint32_t es = hadd2(hadd2(v.x, v.y), hadd2(v.z, v.w));
      const float w = exp_e(es);
      mx = habsmax2(mx, es);
      l += w;
      a = fmaf(w, h_hi(es), a);
    };
    const bool last = e + 2 >= n_c;
    if (last) named_bar_sync(13 + (e & 1), 160);
    else mbar_wait(sbase + OFF_BAR + 80 + 8 * e, 0);
    {
      uint4 v[6];
      static_for<0, 6>([&](auto Qc) { v[decltype(Qc)::value] = lds128<decltype(Qc)::value * 512>(ea); });
      sched_fence(ck, tid >> 10);
#pragma unroll
      for (int q = 0; q < 6; q++) take(v[q]);
    }
    __nv_bfloat16* op = late.out + b0 + e;
    asm volatile("" : "+l"(op));
    if (last) named_bar_sync(10 + (e & 1), 160);
    take(lds128<3072>(ea));
    take(lds128<3072 + 512>(ea));
    asm volatile("" : "+f"(l), "+f"(a), "+r"(mx));
    sched_fence(ck, tid >> 10);
    asm volatile("{\n.reg .pred p, q;\nsetp.ne.u32 q, %1, 0;\nsetp.eq.and.u32 p|q, %0, 0, q;\n@p bar.sync 8, 160;\n@q bar.sync 9, 160;\n}"
                 ::"r"(e & 1), "r"((uint32_t)last) : "memory");
    {
      const uint4 v0 = lds128<4096>(ea + ck), v1 = lds128<4096 + 512>(ea);
      take(v0);
      take(v1);
    }
    const uint32_t big = __ballot_sync(0xffffffffu, ds <= fabsf(h_hi(mx)) * (1.f / 16384.f));
    const uint32_t bad = __ballot_sync(0xffffffffu, ((mx & 0x7fffu) > 0x7000u) | ((mx & 0x7c000000u) == 0x7c000000u));
    const bool ok = (big != 0u) & (bad == 0u) & ok_cta;
#pragma unroll
    for (int o = 0; o < 5; o++) {
      l += __uint_as_float(shfl_xor_v(__float_as_uint(l), 1 << o));
      a += __uint_as_float(shfl_xor_v(__float_as_uint(a), 1 << o));
    }
    float r;
    asm("rcp.approx.ftz.f32 %0, %1;" : "=f"(r) : "f"(l));
    if (lane == 0 && e < n_out) *op = __float2bfloat16_rn(a * 0.0625f * r);
    if (!ok && e < n_out)
      general_element(idx + (b0 + e) * kF, table, late.ii, late.jj, W, late.vec[0], late.vec[1], late.vec[2], op, reinterpret_cast<float*>(smem + OFF_EMB + e * kElem));
  }
}

__global__ void __launch_bounds__(kThreads, 1)
afm_kernel(const int* __restrict__ idx, const __nv_bfloat16* __restrict__ table, const __nv_bfloat16* __restrict__ W,
           uint32_t ix_stride, uint32_t ix_bias, uint32_t ix_last, int per, int n_elem, int n_left,
           const __grid_constant__ Late late) {
  extern __shared__ __align__(1024) uint8_t smem[];
  constexpr uint32_t sbase = 0x400u;

  const int tid = threadIdx.x;
  const int t = tid & 127;
  const int lane = tid & 31;
  const int warp = tid >> 5;
  uint32_t ck = 0;
  uint32_t never = tid >> 10;
  const int grp = 7 - (t >> 4);
  const bool v01 = grp < 7, v23 = grp < 6;
  const bool is_left = (int)blockIdx.x < n_left;
  const uint32_t ioff = blockIdx.x * ix_stride - ix_bias + ((tid >> 7) * kF + 4 * grp) * 4;
  uint2 gi01, gi23;
  ldg_idx4(gi01, gi23, idx, ioff <= ix_last ? ioff : 0u, v01 && tid < 256, v23 && tid < 256);
  asm volatile("{\n.reg .pred p;\nsetp.ge.u32 p, %1, %2;\n@p prefetch.global.L2 [%0];\n}" ::"l"(W + ((blockIdx.x * 32 + tid) & 255) * 64), "r"(tid), "n"(384 - 32) : "memory");
  sched_fence(ck, never);
  const int wq = warp & 3;
  const int wg = __shfl_sync(0xffffffffu, tid >> 7, 0);
  const int n_c = max(min(per, n_elem - ((int)blockIdx.x - n_left) * per), 2);
  const __nv_bfloat16* gsrc = table + (t & 15) * 8;
  asm volatile("" : "+l"(gsrc));
  uint32_t cv_ptr = sbase + OFF_EMB + wg * kElem + 4 * grp * kRow + (t & 15) * 16;

  if (wg < 2) {
    const int c = lane & 3;
    const int tau = t >> 2;
    if (wg == 0) {
      asm volatile("cp.async.ca.shared.global [%0], [%1], 4;\ncp.async.ca.shared.global [%0+4], [%2], 4;\ncp.async.commit_group;"
                   ::"r"(sbase + OFF_ES + t * 8), "l"(late.vec[t >> 6] + 2 * (t & 63)), "l"(late.vec[2] + 2 * (t & 63)) : "memory");
    }
    const int nb = (n_c - wg + 1) >> 1;
    const uint32_t sc = late.sched.e[tau];
    uint4 g0[4];
    const bool q01 = v01 && !is_left, q23 = v23 && !is_left;
    sched_fence(ck, never);
    if (wg == 1) {
      uint32_t y;
      asm volatile("or.b32 %0, %1, %2;" : "=r"(y) : "r"(gi01.x), "r"(gi23.x));
      const uint32_t t0 = clock32() + (y >> 31);
      while (clock32() - t0 < 450) {
      }
    }
    sched_fence(ck, never);
    g0[0] = ldg_row(gsrc, gi01.x, q01);
    g0[1] = ldg_row(gsrc, gi01.y, q01);
    g0[2] = ldg_row(gsrc, gi23.x, q23);
    g0[3] = ldg_row(gsrc, gi23.y, q23);
    sched_fence(ck, never);
    const int* lip = idx + min((int)(blockIdx.x * 256 + tau * 8 + wg), n_elem - 1) * kF;
    const uint2 li01 = ldg64p(lip, is_left), li23 = ldg64p(lip + 2, is_left);
    if (warp == 0) {
      if (lane == 0) {
#pragma unroll
        for (int i = 0; i < 16; i++) mbar_init(sbase + OFF_BAR + 8 * i, i < 2 ? 1 : i < 8 ? 4 : 128);
        mbar_arrive(sbase + OFF_BAR);
        mbar_arrive(sbase + OFF_BAR + 8);
      }
      if (smem_u32(smem) != sbase) __trap();
      __syncwarp();
      named_bar_arrive(6, 160);
    }
    if (wg == 0) {
      asm volatile("cp.async.wait_group 0;" ::: "memory");
      const uint32_t s0 = lds32(sbase + OFF_ES + t * 8), s1 = lds32(sbase + OFF_ES + t * 8 + 4);
      sts32(sbase + OFF_VEC + ((t & 112u) | ((t & 3u) << 2) | ((t >> 2) & 3u)) * 4,
            bf2h_x16(s0) ^ (t < 64 ? 0x80008000u : 0u));
      sts32(sbase + OFF_VEC + 512 + (t & 63) * 4, bf2h_x16(s1));
      named_bar_arrive(12, 256);
    }
    asm volatile("{\n.reg .pred p;\nsetp.eq.u32 p, %0, 0;\n@p bar.sync 1, 128;\n@!p bar.sync 12, 256;\n}" ::"r"(wg) : "memory");
    sched_fence(ck, never);
    uint32_t bs[16], hs[16], ps[16];
    load_vec(ps, sbase + OFF_VEC + 512 + c * 16);
    load_vec(bs, sbase + OFF_VEC + c * 16);
    load_vec(hs, sbase + OFF_VEC + 256 + c * 16);
    sched_fence(ck, never);
    if (wg == 1) named_bar_sync(7, 256);
    asm volatile("setmaxnreg.inc.sync.aligned.u32 %0;" ::"n"(216));
    if (wg == 0) named_bar_arrive(7, 256);
    uint32_t pt_ptr = shfl_xor<0>(sbase + OFF_ES + (2 + wg) * ES_STRIDE + t * 4);
    never = pt_ptr >> 31;
    uint32_t ra[6];
#pragma unroll
    for (int r = 0; r < 6; r++) ra[r] = sbase + OFF_EMB + wg * kElem + c * 16 + ((sc >> (5 * r)) & 31u) * kRow;
    asm volatile("" : "+r"(ra[0]), "+r"(ra[1]), "+r"(ra[2]), "+r"(ra[3]), "+r"(ra[4]), "+r"(ra[5]));
    sched_fence(ck, never);
    uint32_t Af[32], acc[32], S0[16], S1[16], S2[16], S3[16];
    constexpr uint64_t dB = (uint64_t)(((sbase + OFF_B) & 0x3FFFFu) >> 4) | ((uint64_t)(B_NBLK >> 4) << 16) |
                            ((uint64_t)(1024 >> 4) << 32) | ((uint64_t)1 << 62);
    auto products = [&](const uint32_t (&X)[16], const uint32_t (&Y)[16], const uint32_t (&Z)[16]) {
#pragma unroll
      for (int i = 0; i < 16; i++) {
        Af[2 * i] = hmul2(X[i], Z[i]);
        Af[2 * i + 1] = hmul2(Y[i], Z[i]);
      }
    };
    auto mma_tile = [&]() {
      fence_regs(Af);
      wgmma_fence();
#pragma unroll
      for (int s = 0; s < 8; s++) {
        const uint64_t d = dB + (uint64_t)(s * (2048 >> 4));
        if (s == 0) wgmma_rs_n128<0>(acc, Af[0], Af[1], Af[2], Af[3], d);
        else wgmma_rs_n128<1>(acc, Af[4 * s], Af[4 * s + 1], Af[4 * s + 2], Af[4 * s + 3], d);
      }
      wgmma_commit();
    };
    auto issue = [&]() {
      mma_tile();
      bar_arrive2<5, 4>(wg);
    };
    uint32_t eh0 = 0, eh1 = 0, sh0 = 0, sh1 = 0;
    auto fold = [&]() {
      eh0 = hadd2(__byte_perm(eh0, sh0, 0x5410), __byte_perm(eh0, sh0, 0x7632));
      eh1 = hadd2(__byte_perm(eh1, sh1, 0x5410), __byte_perm(eh1, sh1, 0x7632));
    };
    auto s_chain = [&]() {
      sh0 = hmul2(Af[0], ps[0]);
      sh1 = hmul2(Af[1], ps[0]);
#pragma unroll
      for (int i = 1; i < 16; i++) {
        sh0 = hfma2(Af[2 * i], ps[i], sh0);
        sh1 = hfma2(Af[2 * i + 1], ps[i], sh1);
      }
      asm volatile("" : "+r"(sh0), "+r"(sh1)::"memory");
    };
    auto epilogue = [&]() {
      wgmma_wait<0>();
      fence_regs(acc);
      fence_regs(S0); fence_regs(S1); fence_regs(S2); fence_regs(S3);
      eh0 = hmul2(bias_relu2(acc[0], bs[0]), hs[0]);
      eh1 = hmul2(bias_relu2(acc[1], bs[0]), hs[0]);
#pragma unroll
      for (int i = 1; i < 16; i++) {
        eh0 = hfma2(bias_relu2(acc[2 * i], bs[i]), hs[i], eh0);
        eh1 = hfma2(bias_relu2(acc[2 * i + 1], bs[i]), hs[i], eh1);
      }
      asm volatile("" : "+r"(eh0), "+r"(eh1)::"memory");
    };
    if (is_left) {
      if (wg == 1) named_bar_arrive(4, 256);
      const int e0 = shfl_xor<0>(blockIdx.x * 256 + tau * 8 + wg);
      const __nv_bfloat16* lsrc = table + c * 8;
      uint32_t ia, ib, ic, id, ma;
      float lsum = 0.f, asum = 0.f;
      auto load_ix = [&](int r) {
        const int* ip = idx + min(e0 + 2 * r, n_elem - 1) * kF;
        const uint2 x = ldg64(ip), y = ldg64(ip + 2);
        ia = x.x; ib = x.y; ic = y.x; id = y.y;
      };
      auto load_row = [&](uint32_t (&v)[16], uint32_t row) {
#pragma unroll
        for (int kb = 0; kb < 4; kb++) {
          const uint4 x = ldg_row(lsrc + 32 * kb, row, true);
          v[4 * kb] = x.x; v[4 * kb + 1] = x.y; v[4 * kb + 2] = x.z; v[4 * kb + 3] = x.w;
        }
      };
      auto cvt_row = [&](uint32_t (&v)[16]) {
#pragma unroll
        for (int i = 0; i < 16; i++) v[i] = bf2h(v[i]);
      };
      auto finish = [&](bool one_row) {
        s_chain();
        sched_fence(ck, never);
        epilogue();
        fold();
        uint32_t es = hadd2((c & 1) ? eh1 : eh0, shfl_xor<1>((c & 1) ? eh0 : eh1));
        es = hadd2(es, shfl_xor<2>(es));
        const float w = one_row && (c & 1) ? 0.f : exp_e(es);
        ma = habsmax2(ma, es);
        lsum += w;
        asum = fmaf(w, h_hi(es), asum);
        sched_fence(ck, never);
      };
      ia = li01.x; ib = li01.y; ic = li23.x; id = li23.y;
      load_row(S0, ia); load_row(S1, ib); load_row(S2, ic); load_row(S3, id);
      if (wg == 0) named_bar_sync(3, 256);
#pragma unroll 1
      for (int r = 0; r < 4; r++) {
        const int e = e0 + 2 * r;
        load_ix(r + 1);
        lsum = 0.f; asum = 0.f; ma = 0;
        cvt_row(S0); cvt_row(S1);
        products(S0, S0, S1);
        bar_sync2<4, 5>(wg);
        issue();
        cvt_row(S2); cvt_row(S3);
        finish(true);
        products(S0, S1, S2);
        bar_sync2<4, 5>(wg);
        issue();
        load_row(S2, ic);
        finish(false);
        products(S0, S1, S3);
        bar_sync2<4, 5>(wg);
        issue();
        load_row(S0, ia); load_row(S1, ib); load_row(S3, id);
        finish(false);
        lsum += __shfl_xor_sync(0xffffffffu, lsum, 1);
        asum += __shfl_xor_sync(0xffffffffu, asum, 1);
        ma = habsmax2(ma, shfl_xor<1>(ma));
        if ((ma & 0x7fffu) > 0x7000u || ((ma >> 16) & 0x7fffu) >= 0x7c00u) lsum = __int_as_float(0x7fffffff);
        if (c == 0 && e < n_elem)
          asm volatile("{\n.reg .b64 v;\nmov.b64 v, {%1,%2};\nst.volatile.global.b64 [%0], v;\n}" ::"l"(g_left + e + ck), "f"(lsum), "f"(asum) : "memory");
      }
      if (wg == 0) named_bar_sync(4, 256);
      return;
    }
    sts128p<0>(cv_ptr, convert_f(g0[0]), v01);
    sts128p<kRow>(cv_ptr, convert_f(g0[1]), v01);
    sts128p<2 * kRow>(cv_ptr, convert_f(g0[2]), v23);
    sts128p<3 * kRow>(cv_ptr, convert_f(g0[3]), v23);
    asm volatile("{\n.reg .pred p;\nsetp.eq.u32 p, %0, 0;\n@p bar.sync 3, 256;\n@!p bar.sync 2, 128;\n}" ::"r"(wg) : "memory");

    static_for<0, 4>([&](auto Kc) {
      constexpr int kb = decltype(Kc)::value;
      const uint4 z = lds128<64 * kb>(ra[5]), x = lds128<64 * kb>(ra[0]), y = lds128<64 * kb>(ra[1]);
      S3[4 * kb] = z.x; S3[4 * kb + 1] = z.y; S3[4 * kb + 2] = z.z; S3[4 * kb + 3] = z.w;
      S0[4 * kb] = x.x; S0[4 * kb + 1] = x.y; S0[4 * kb + 2] = x.z; S0[4 * kb + 3] = x.w;
      S1[4 * kb] = y.x; S1[4 * kb + 1] = y.y; S1[4 * kb + 2] = y.z; S1[4 * kb + 3] = y.w;
      if (kb & 1) sched_fence(ck, never);
    });
#pragma unroll
    for (int i = 0; i < 16; i++) S2[i] = 0;
    static_for<0, 2>([&](auto Hc) {
      constexpr int h = decltype(Hc)::value, n = 16 / 2;
#pragma unroll
      for (int i = h * n; i < h * n + n; i++) {
        Af[2 * i] = hmul2(S0[i], S3[i]);
        Af[2 * i + 1] = hmul2(S1[i], S3[i]);
        asm volatile("" : "+r"(Af[2 * i]), "+r"(Af[2 * i + 1])::"memory");
      }
      if (h == 0) {
        if (wg == 1) named_bar_sync(5, 256);
        sched_fence(ck, never);
      }
      wgmma_fence();
#pragma unroll
      for (int s = h * n / 2; s < (h * n + n) / 2; s++) {
        const uint64_t d = dB + (uint64_t)(s * (2048 >> 4));
        if (s == 0) wgmma_rs_n128<0>(acc, Af[0], Af[1], Af[2], Af[3], d);
        else wgmma_rs_n128<1>(acc, Af[4 * s], Af[4 * s + 1], Af[4 * s + 2], Af[4 * s + 3], d);
      }
      sched_fence(ck, never);
    });
    wgmma_commit();
    bar_arrive2<5, 4>(wg);
    sched_fence(ck, never);

    auto bump = [&](uint32_t& r) { asm volatile("add.u32 %0, %0, %1;" : "+r"(r) : "n"(2 * kElem)); };
    int left = nb - 1;
    ra[0] += 2 * kElem; ra[1] += 2 * kElem; ra[5] += 2 * kElem;
    uint4 r0, r1;
    uint32_t el = wg, rdy = 0;
    auto tile = [&](auto Tc) {
      constexpr int tt = decltype(Tc)::value & 7;
      constexpr bool last = decltype(Tc)::value > 7;
      sched_fence(ck, never);
      fold();
      const uint32_t f0 = eh0, f1 = eh1;
      sts32o<(tt == 0 ? 4096 - 2 * ES_STRIDE : (tt - 1) * 1024)>(pt_ptr, eh0);
      sts32o<(tt == 0 ? 4096 - 2 * ES_STRIDE : (tt - 1) * 1024) + 512>(pt_ptr, eh1);
      if (tt == 0) mbar_arrive(sbase + OFF_BAR + 64 + 8 * el);
      if (last) bar_arrive2<13, 14, 160>(wg);
      if (tt == 2) rdy = mbar_test(sbase + OFF_BAR + 8 * min(el + 2, n_c - 1), 0);
      sched_fence(ck, never);
      if (tt == 0) load_vec(S0, ra[3]);
      if (tt == 1) load_vec(S2, ra[4]);
      if (tt == 2) load_vec(S1, ra[2]);
      if (tt == 3 && !last) {
        load_vec(S0, ra[0]);
        r0 = lds128<0>(ra[1]);
        r1 = lds128<64>(ra[1]);
      }
      if (tt == 4) {
        load_vec(S3, ra[5]);
        const uint4 v2 = lds128<128>(ra[1]), v3 = lds128<192>(ra[1]);
        S1[8] = v2.x; S1[9] = v2.y; S1[10] = v2.z; S1[11] = v2.w; S1[12] = v3.x; S1[13] = v3.y; S1[14] = v3.z; S1[15] = v3.w;
        S1[0] = r0.x; S1[1] = r0.y; S1[2] = r0.z; S1[3] = r0.w; S1[4] = r1.x; S1[5] = r1.y; S1[6] = r1.z; S1[7] = r1.w;
      }
      sched_fence(ck, never);
      s_chain();
      sched_fence(ck, never);
      epilogue();
      sched_fence(ck, never);
      if (tt == 2 && !rdy) mbar_wait(sbase + OFF_BAR + 8 * min(el + 2, n_c - 1), 0);
      if (tt == 0) { products(S1, S3, S0); bump(ra[3]); }
      if (tt == 1) { products(S1, S0, S2); bump(ra[4]); }
      if (tt == 2) { products(S0, S2, S1); bump(ra[2]); }
      if (tt == 3) products(S1, S2, S3);
      if (tt == 4) {
        products(S0, S1, S3);
        bump(ra[0]); bump(ra[1]); bump(ra[5]);
        asm volatile("add.u32 %0, %0, %1;" : "+r"(pt_ptr) : "n"(2 * ES_STRIDE));
        el += 2;
      }
      sched_fence(ck, never);
      keep2(ck, f0, f1, never);
      if (!last) {
        bar_sync2<4, 5>(wg);
        issue();
      }
    };
#pragma unroll 1
    for (;;) {
      tile(std::integral_constant<int, 0>{});
      tile(std::integral_constant<int, 1>{});
      tile(std::integral_constant<int, 2>{});
      if (left == 0) break;
      tile(std::integral_constant<int, 3>{});
      tile(std::integral_constant<int, 4>{});
      left--;
    }
    tile(std::integral_constant<int, 8 + 3>{});
    fold();
    sts32o<3072>(pt_ptr, eh0);
    sts32o<3072 + 512>(pt_ptr, eh1);
    bar_arrive2<10, 11, 160>(wg);
    s_chain();
    sched_fence(ck, never);
    bar_sync2<4, 5>(wg);
    uint32_t al[24], ah[8];
    fence_regs(Af);
    wgmma_fence();
#pragma unroll
    for (int s = 0; s < 8; s++) {
      const uint64_t d = dB + (uint64_t)(s * (2048 >> 4));
      if (s == 0) wgmma_rs_n96<0>(al, Af[0], Af[1], Af[2], Af[3], d);
      else wgmma_rs_n96<1>(al, Af[4 * s], Af[4 * s + 1], Af[4 * s + 2], Af[4 * s + 3], d);
    }
    wgmma_commit();
    bar_arrive2<5, 4>(wg);
#pragma unroll
    for (int s = 0; s < 8; s++) {
      const uint64_t d = dB + (uint64_t)(s * (2048 >> 4) + ((B_NBLK + 64) >> 4));
      if (s == 0) wgmma_rs_n32<0>(ah, Af[0], Af[1], Af[2], Af[3], d);
      else wgmma_rs_n32<1>(ah, Af[4 * s], Af[4 * s + 1], Af[4 * s + 2], Af[4 * s + 3], d);
    }
    wgmma_commit();
    wgmma_wait<1>();
    fence_regs(al);
    eh0 = hmul2(bias_relu2(al[0], bs[0]), hs[0]);
    eh1 = hmul2(bias_relu2(al[1], bs[0]), hs[0]);
#pragma unroll
    for (int i = 1; i < 12; i++) {
      eh0 = hfma2(bias_relu2(al[2 * i], bs[i]), hs[i], eh0);
      eh1 = hfma2(bias_relu2(al[2 * i + 1], bs[i]), hs[i], eh1);
    }
    asm volatile("" : "+r"(eh0), "+r"(eh1)::"memory");
    sched_fence(ck, never);
    wgmma_wait<0>();
    fence_regs(ah);
#pragma unroll
    for (int i = 0; i < 4; i++) {
      eh0 = hfma2(bias_relu2(ah[2 * i], bs[12 + i]), hs[12 + i], eh0);
      eh1 = hfma2(bias_relu2(ah[2 * i + 1], bs[12 + i]), hs[12 + i], eh1);
    }
    fold();
    sts32o<4096>(pt_ptr + ck, eh0);
    sts32o<4096 + 512>(pt_ptr, eh1);
    bar_arrive2<8, 9, 160>(wg);
    sched_fence(ck, never);
    if (wg == 0) {
      named_bar_sync(4, 256);
    } else if (n_c & 1) {
      for (int i = 0; i < 5; i++) {
        named_bar_sync(5, 256);
        named_bar_arrive(4, 256);
      }
    }
  } else {
    {
      asm volatile("setmaxnreg.dec.sync.aligned.u32 104;");
      uint4 wr[16];
#pragma unroll
      for (int r = 0; r < 16; r++) wr[r] = ldg128(W + (32 * wq + 2 * r) * kD + 8 * lane);
      const uint32_t wa = sbase + OFF_B + ((lane >> 3) & 1) * B_NBLK + wq * 4096 + (lane >> 4) * 128;
      const uint32_t lx = (lane & 7) ^ (lane >> 4);
      uint32_t wad[4], mw = 0;
#pragma unroll
      for (int x = 0; x < 4; x++) wad[x] = wa + ((lx ^ (2 * x)) << 4);
      sched_fence(ck, never);
      static_for<0, 16>([&](auto Rc) {
        constexpr int r = decltype(Rc)::value;
        uint4 v;
        v.x = bf2h_x16(wr[r].x); v.y = bf2h_x16(wr[r].y); v.z = bf2h_x16(wr[r].z); v.w = bf2h_x16(wr[r].w);
        sts128<(r & 3) * 1024 + (r >> 2) * 256>(wad[r >> 2], v);
        mw = babsmax2(babsmax2(mw, wr[r].x), babsmax2(wr[r].y, babsmax2(wr[r].z, wr[r].w)));
        if (r == 3) sched_fence(ck, never);
        if (r == 7 || r == 11) sched_fence(ck, never);
      });
      sched_fence(ck, never);
      fence_proxy_async();
      named_bar_arrive(3, 256);
      sched_fence(ck, never);
      sts32p(sbase + OFF_STAT + wq * 4 + ck, redux_max(absmax_bits(mw)), lane == 0);
    }
    named_bar_sync(15, 128);
    asm volatile("setmaxnreg.dec.sync.aligned.u32 %0;" ::"n"(504 - 2 * 216));
    if ((int)blockIdx.x >= n_left) helper_rest(idx, table, W, late, per, n_elem, n_left, smem);
    else {
      named_bar_sync(6, 160);
#pragma unroll 1
      for (int q = 2; q < 8; q++) {
        const int e = min((int)blockIdx.x * 256 + (t >> 2) * 8 + q, n_elem - 1);
        const uint32_t row = ldg32(idx + e * kF + (t & 3));
        asm volatile("prefetch.global.L2 [%0];\nprefetch.global.L2 [%0+128];" ::"l"(table + (size_t)row * kD) : "memory");
      }
    }
  }
}

}

extern "C" void kernel_launch(void* const* d_in, const int* in_sizes, int n_in, void* d_out, int out_size) {
  const int* idx = (const int*)d_in[0];
  const __nv_bfloat16* table = (const __nv_bfloat16*)d_in[1];
  const int* ii = (const int*)d_in[2];
  const int* jj = (const int*)d_in[3];
  const __nv_bfloat16* W = (const __nv_bfloat16*)d_in[4];
  const __nv_bfloat16* bias = (const __nv_bfloat16*)d_in[5];
  const __nv_bfloat16* hvec = (const __nv_bfloat16*)d_in[6];
  const __nv_bfloat16* pvec = (const __nv_bfloat16*)d_in[7];
  __nv_bfloat16* out = (__nv_bfloat16*)d_out;
  const int B = out_size;

  static int num_sms = 0;
  if (num_sms == 0) {
    int dev = 0;
    cudaGetDevice(&dev);
    cudaDeviceGetAttribute(&num_sms, cudaDevAttrMultiProcessorCount, dev);
    cudaFuncSetAttribute(afm_kernel, cudaFuncAttributeMaxDynamicSharedMemorySize, SMEM_BYTES);
  }
  const Sched sched = {{
    0x2d2cb011u, 0x2c9a0662u, 0x2876c228u, 0x26074141u, 0x2655c878u, 0x2985dc43u, 0x18722403u, 0x22299aaeu,
    0x02a6b0b1u, 0x30d73d00u, 0x00941af1u, 0x2ee29c4au, 0x2ad5a410u, 0x21250923u, 0x328a84aeu, 0x0d780599u,
    0x324551f8u, 0x3112a583u, 0x062ca4eeu, 0x155360e3u, 0x1cb204d6u, 0x1f4280c9u, 0x2776e487u, 0x090b60a2u,
    0x2413bf17u, 0x168b28ecu, 0x10c78a70u, 0x2f578ed1u, 0x1a334ac2u, 0x0888c875u, 0x1d5a3249u, 0x2305bf2au
  }};
  for (int off = 0; off < B; off += kMaxChunk) {
    const int n = B - off < kMaxChunk ? B - off : kMaxChunk;
    const int n_left = (n + 255) / 256;
    const int room = num_sms - n_left > 1 ? num_sms - n_left : 1;
    int per = (n + room - 1) / room;
    if (per > kMaxB) per = kMaxB;
    const int n_main = (n + per - 1) / per;
    const Late late = {{bias, hvec, pvec, pvec}, ii, jj, out + off, sched};
    afm_kernel<<<n_left + n_main, kThreads, SMEM_BYTES>>>(idx + (size_t)off * kF, table, W, per * kF * 4, n_left * per * kF * 4,
                                                          (n * kF - 2) * 4, per, n, n_left, late);
  }
}
```

```cpp
#include <cuda_runtime.h>
#include <cuda_bf16.h>
#include <cuda_fp16.h>
#include <stdint.h>
#include <type_traits>

namespace {

constexpr int kF = 26;
constexpr int kD = 128;
constexpr int kP = 325;
constexpr int kMaxB = 8;
constexpr int kThreads = 384;
constexpr int kRow = 320;
constexpr int kElem = kF * kRow;

constexpr int B_NBLK = 16 * 1024;
constexpr int OFF_B = 0;
constexpr int OFF_EMB = 2 * B_NBLK;
constexpr int OFF_ES = OFF_EMB + kMaxB * kElem;
constexpr int ES_STRIDE = 5 * 1024;
constexpr int OFF_VEC = OFF_ES + (kMaxB + 2) * ES_STRIDE;
constexpr int OFF_STAT = OFF_VEC + 768;
constexpr int OFF_BAR = OFF_STAT + 128;
constexpr int SMEM_USED = OFF_BAR + 128;
static_assert(OFF_EMB + (kMaxB + 2) * kElem <= SMEM_USED, "unused operand prefetches run up to 2 elements past the end");
constexpr int SMEM_BYTES = SMEM_USED;
static_assert(OFF_ES % 16 == 0 && OFF_VEC % 16 == 0 && OFF_STAT % 16 == 0 && kElem % 128 == 0, "alignment");

struct Sched { uint32_t e[32]; };
struct Late {
  const __nv_bfloat16* vec[4];
  const int* ii;
  const int* jj;
  __nv_bfloat16* out;
  Sched sched;
};

constexpr int kMaxChunk = 8192;
__device__ float2 g_left[kMaxChunk];

__device__ __forceinline__ uint32_t smem_u32(const void* p) { return (uint32_t)__cvta_generic_to_shared(p); }
__device__ __forceinline__ void named_bar_sync(int id, int n) { asm volatile("bar.sync %0, %1;" ::"r"(id), "r"(n) : "memory"); }
__device__ __forceinline__ void named_bar_arrive(int id, int n) { asm volatile("bar.arrive %0, %1;" ::"r"(id), "r"(n) : "memory"); }
template <int A, int B>
__device__ __forceinline__ void bar_sync2(uint32_t sel) {
  asm volatile("{\n.reg .pred p;\nsetp.eq.u32 p, %0, 0;\n@p bar.sync %1, 256;\n@!p bar.sync %2, 256;\n}" ::"r"(sel), "n"(A), "n"(B) : "memory");
}
template <int A, int B, int N = 256>
__device__ __forceinline__ void bar_arrive2(uint32_t sel) {
  asm volatile("{\n.reg .pred p;\nsetp.eq.u32 p, %0, 0;\n@p bar.arrive %1, %3;\n@!p bar.arrive %2, %3;\n}" ::"r"(sel), "n"(A), "n"(B), "n"(N) : "memory");
}
__device__ __forceinline__ void mbar_init(uint32_t bar, uint32_t count) {
  asm volatile("mbarrier.init.shared::cta.b64 [%0], %1;" ::"r"(bar), "r"(count) : "memory");
}
__device__ __forceinline__ void mbar_arrive(uint32_t bar) {
  asm volatile("mbarrier.arrive.shared::cta.b64 _, [%0];" ::"r"(bar) : "memory");
}
__device__ __forceinline__ void mbar_arrive_p(uint32_t bar, bool on) {
  asm volatile("{\n.reg .pred p;\nsetp.ne.u32 p, %1, 0;\n@p mbarrier.arrive.shared::cta.b64 _, [%0];\n}" ::"r"(bar), "r"((uint32_t)on) : "memory");
}
__device__ __forceinline__ uint32_t mbar_test(uint32_t bar, uint32_t parity) {
  uint32_t ok;
  asm volatile("{\n.reg .pred p;\nmbarrier.test_wait.parity.shared::cta.b64 p, [%1], %2;\nselp.u32 %0, 1, 0, p;\n}\n"
               : "=r"(ok) : "r"(bar), "r"(parity) : "memory");
  return ok;
}
__device__ __forceinline__ void mbar_wait(uint32_t bar, uint32_t parity) {
  uint32_t ok, it = 0;
  do {
    asm volatile("{\n.reg .pred p;\nmbarrier.try_wait.parity.shared::cta.b64 p, [%1], %2, %3;\nselp.u32 %0, 1, 0, p;\n}\n"
                 : "=r"(ok) : "r"(bar), "r"(parity), "r"(20000) : "memory");
  } while (!ok && ++it < (1u << 16));
}
__device__ __forceinline__ void wgmma_fence() { asm volatile("wgmma.fence.sync.aligned;" ::: "memory"); }
__device__ __forceinline__ void wgmma_commit() { asm volatile("wgmma.commit_group.sync.aligned;" ::: "memory"); }
template <int N>
__device__ __forceinline__ void wgmma_wait() { asm volatile("wgmma.wait_group.sync.aligned %0;" ::"n"(N) : "memory"); }
__device__ __forceinline__ void fence_proxy_async() { asm volatile("fence.proxy.async.shared::cta;" ::: "memory"); }

__device__ __forceinline__ uint32_t hmul2(uint32_t a, uint32_t b) {
  uint32_t d;
  asm("mul.rn.f16x2 %0, %1, %2;" : "=r"(d) : "r"(a), "r"(b));
  return d;
}
__device__ __forceinline__ uint32_t hadd2(uint32_t a, uint32_t b) {
  uint32_t d;
  asm("add.rn.f16x2 %0, %1, %2;" : "=r"(d) : "r"(a), "r"(b));
  return d;
}
__device__ __forceinline__ uint32_t hfma2(uint32_t a, uint32_t b, uint32_t c) {
  uint32_t d;
  asm("fma.rn.f16x2 %0, %1, %2, %3;" : "=r"(d) : "r"(a), "r"(b), "r"(c));
  return d;
}
__device__ __forceinline__ uint32_t bias_relu2(uint32_t x, uint32_t nb) {
  uint32_t d;
  asm("max.NaN.f16x2 %0, %1, %2;" : "=r"(d) : "r"(x), "r"(nb));
  return d;
}
__device__ __forceinline__ uint32_t habsmax2(uint32_t a, uint32_t b) {
  uint32_t d;
  asm("max.NaN.xorsign.abs.f16x2 %0, %1, %2;" : "=r"(d) : "r"(a), "r"(b));
  return d;
}
__device__ __forceinline__ uint32_t babsmax2(uint32_t a, uint32_t b) {
  uint32_t d;
  asm("max.NaN.xorsign.abs.bf16x2 %0, %1, %2;" : "=r"(d) : "r"(a), "r"(b));
  return d;
}
__device__ __forceinline__ uint32_t bf2h(uint32_t x) {
  uint32_t d;
  asm("cvt.rn.f16x2.f32 %0, %1, %2;" : "=r"(d) : "f"(__uint_as_float(x & 0xffff0000u)), "f"(__uint_as_float(x << 16)));
  return d;
}
__device__ __forceinline__ uint32_t bf2h_x16(uint32_t x) {
  uint32_t hi, lo, d;
  asm("fma.rn.bf16x2 %0, %1, %2, %3;" : "=r"(hi) : "r"(x), "r"(0x41800000u), "r"(0u));
  asm("{\n.reg .b16 l, h;\n.reg .b32 t;\nmov.b32 {l, h}, %1;\nmov.b32 t, {l, l};\nfma.rn.bf16x2 %0, t, %2, %3;\n}"
      : "=r"(lo) : "r"(x), "r"(0x41800000u), "r"(0u));
  asm("cvt.rn.f16x2.f32 %0, %1, %2;" : "=r"(d) : "f"(__uint_as_float(hi)), "f"(__uint_as_float(lo)));
  return d;
}
template <bool HI_FMA>
__device__ __forceinline__ uint32_t bf2h_f(uint32_t x) {
  uint32_t hi = x & 0xffff0000u, lo, d;
  if (HI_FMA) asm("fma.rn.bf16x2 %0, %1, %2, %3;" : "=r"(hi) : "r"(x), "r"(0x3f800000u), "r"(0u));
  asm("{\n.reg .b16 l, h;\n.reg .b32 t;\nmov.b32 {l, h}, %1;\nmov.b32 t, {l, l};\nfma.rn.bf16x2 %0, t, %2, %3;\n}"
      : "=r"(lo) : "r"(x), "r"(0x3f800000u), "r"(0u));
  asm("cvt.rn.f16x2.f32 %0, %1, %2;" : "=r"(d) : "f"(__uint_as_float(hi)), "f"(__uint_as_float(lo)));
  return d;
}
__device__ __forceinline__ uint4 convert(uint4 v) { return make_uint4(bf2h(v.x), bf2h(v.y), bf2h(v.z), bf2h(v.w)); }
__device__ __forceinline__ uint4 convert_f(uint4 v) {
  return make_uint4(bf2h_f<false>(v.x), bf2h_f<true>(v.y), bf2h_f<false>(v.z), bf2h_f<true>(v.w));
}
__device__ __forceinline__ float h_lo(uint32_t x) { return __half2float(__ushort_as_half((unsigned short)(x & 0xffffu))); }
__device__ __forceinline__ float h_hi(uint32_t x) { return __half2float(__ushort_as_half((unsigned short)(x >> 16))); }
__device__ __forceinline__ uint32_t redux_max(uint32_t v) {
  uint32_t d;
  asm volatile("redux.sync.max.u32 %0, %1, 0xffffffff;" : "=r"(d) : "r"(v));
  return d;
}
__device__ __forceinline__ uint32_t absmax_bits(uint32_t m) { return max(m & 0x7fffu, (m >> 16) & 0x7fffu); }

template <int OFF>
__device__ __forceinline__ uint4 lds128(uint32_t addr) {
  uint4 v;
  asm volatile("ld.shared.v4.u32 {%0,%1,%2,%3}, [%4+%5];" : "=r"(v.x), "=r"(v.y), "=r"(v.z), "=r"(v.w) : "r"(addr), "n"(OFF));
  return v;
}
template <int OFF>
__device__ __forceinline__ void sts128(uint32_t addr, uint4 v) {
  asm volatile("st.shared.v4.u32 [%0+%5], {%1,%2,%3,%4};" ::"r"(addr), "r"(v.x), "r"(v.y), "r"(v.z), "r"(v.w), "n"(OFF) : "memory");
}
__device__ __forceinline__ uint32_t lds32(uint32_t addr) {
  uint32_t v;
  asm volatile("ld.shared.u32 %0, [%1];" : "=r"(v) : "r"(addr));
  return v;
}
__device__ __forceinline__ void sts32(uint32_t addr, uint32_t v) { asm volatile("st.shared.u32 [%0], %1;" ::"r"(addr), "r"(v) : "memory"); }
__device__ __forceinline__ uint32_t ldg32(const void* p) {
  uint32_t v;
  asm volatile("ld.global.u32 %0, [%1];" : "=r"(v) : "l"(p) : "memory");
  return v;
}
__device__ __forceinline__ uint4 ldg128(const void* p) {
  uint4 v;
  asm volatile("ld.global.v4.u32 {%0,%1,%2,%3}, [%4];" : "=r"(v.x), "=r"(v.y), "=r"(v.z), "=r"(v.w) : "l"(p) : "memory");
  return v;
}
__device__ __forceinline__ uint2 ldg64(const void* p) {
  uint2 v;
  asm volatile("ld.global.v2.u32 {%0,%1}, [%2];" : "=r"(v.x), "=r"(v.y) : "l"(p) : "memory");
  return v;
}
__device__ __forceinline__ uint2 ldg64p(const void* p, bool on) {
  uint2 v;
  asm volatile("{\n.reg .pred p;\nsetp.ne.u32 p, %3, 0;\n@p ld.volatile.global.v2.u32 {%0,%1}, [%2];\n}" : "=r"(v.x), "=r"(v.y) : "l"(p), "r"((uint32_t)on) : "memory");
  return v;
}
__device__ __forceinline__ void ldg_idx4(uint2& x, uint2& y, const void* base, uint32_t off, bool on0, bool on1) {
  asm volatile("{\n.reg .pred p, q;\n.reg .b64 a;\n.reg .b32 lo, hi;\nsetp.ne.u32 p, %6, 0;\nsetp.ne.u32 q, %7, 0;\n"
               "mov.b64 {lo, hi}, %4;\nadd.cc.u32 lo, lo, %5;\naddc.u32 hi, hi, 0;\nmov.b64 a, {lo, hi};\n"
               "@p ld.volatile.global.v2.u32 {%0,%1}, [a];\n@q ld.volatile.global.v2.u32 {%2,%3}, [a+8];\n}"
               : "=r"(x.x), "=r"(x.y), "=r"(y.x), "=r"(y.y) : "l"(base), "r"(off), "r"((uint32_t)on0), "r"((uint32_t)on1) : "memory");
}
__device__ __forceinline__ uint4 ldg_row(const void* base, uint32_t row, bool on) {
  uint4 v;
  asm volatile("{\n.reg .pred p;\n.reg .b64 a;\nsetp.ne.u32 p, %6, 0;\nmad.wide.u32 a, %5, 256, %4;\n@p ld.global.v4.u32 {%0,%1,%2,%3}, [a];\n}"
               : "=r"(v.x), "=r"(v.y), "=r"(v.z), "=r"(v.w) : "l"(base), "r"(row), "r"((uint32_t)on) : "memory");
  return v;
}
template <int OFF>
__device__ __forceinline__ void sts128p(uint32_t addr, uint4 v, bool on) {
  asm volatile("{\n.reg .pred p;\nsetp.ne.u32 p, %6, 0;\n@p st.shared.v4.u32 [%0+%5], {%1,%2,%3,%4};\n}"
               ::"r"(addr), "r"(v.x), "r"(v.y), "r"(v.z), "r"(v.w), "n"(OFF), "r"((uint32_t)on) : "memory");
}
__device__ __forceinline__ void sts32p(uint32_t addr, uint32_t v, bool on) {
  asm volatile("{\n.reg .pred p;\nsetp.ne.u32 p, %2, 0;\n@p st.shared.u32 [%0], %1;\n}" ::"r"(addr), "r"(v), "r"((uint32_t)on) : "memory");
}
__device__ __forceinline__ uint32_t shfl_xor_v(uint32_t v, int m) {
  uint32_t d;
  asm volatile("shfl.sync.bfly.b32 %0, %1, %2, 0x1f, 0xffffffff;" : "=r"(d) : "r"(v), "r"(m));
  return d;
}
template <int M>
__device__ __forceinline__ uint32_t shfl_xor(uint32_t v) {
  uint32_t d;
  asm volatile("shfl.sync.bfly.b32 %0, %1, %2, 0x1f, 0xffffffff;" : "=r"(d) : "r"(v), "n"(M));
  return d;
}
template <int I, int N, typename F>
__device__ __forceinline__ void static_for(F&& f) {
  if constexpr (I < N) {
    f(std::integral_constant<int, I>{});
    static_for<I + 1, N>(f);
  }
}
template <int N>
__device__ __forceinline__ void fence_regs(uint32_t (&r)[N]) {
#pragma unroll
  for (int i = 0; i < N; i++) asm volatile("" : "+r"(r[i])::"memory");
}
__device__ __forceinline__ void load_vec(uint32_t (&v)[16], uint32_t a) {
  const uint4 v0 = lds128<0>(a), v1 = lds128<64>(a), v2 = lds128<128>(a), v3 = lds128<192>(a);
  v[0] = v0.x; v[1] = v0.y; v[2] = v0.z; v[3] = v0.w; v[4] = v1.x; v[5] = v1.y; v[6] = v1.z; v[7] = v1.w;
  v[8] = v2.x; v[9] = v2.y; v[10] = v2.z; v[11] = v2.w; v[12] = v3.x; v[13] = v3.y; v[14] = v3.z; v[15] = v3.w;
}

template <int OFF>
__device__ __forceinline__ void sts32o(uint32_t addr, uint32_t v) {
  asm volatile("st.shared.u32 [%0+%2], %1;" ::"r"(addr), "r"(v), "n"(OFF) : "memory");
}
__device__ __forceinline__ void keep2(uint32_t& ck, uint32_t a, uint32_t b, uint32_t never) {
  asm volatile("{\n.reg .pred p;\nsetp.ne.u32 p, %3, 0;\n@p xor.b32 %0, %1, %2;\n}" : "+r"(ck) : "r"(a), "r"(b), "r"(never));
}
__device__ __forceinline__ float exp_e(uint32_t es) {
  float w;
  asm("ex2.approx.ftz.f32 %0, %1;" : "=f"(w) : "f"(h_lo(es) * (1.4426950408889634f / 256.f)));
  return w;
}
__device__ __forceinline__ uint32_t clock32() {
  uint32_t v;
  asm volatile("mov.u32 %0, %%clock;" : "=r"(v)::"memory");
  return v;
}
__device__ __forceinline__ void sched_fence(uint32_t& ck, uint32_t never) {
  asm volatile("{\n.reg .pred p;\nsetp.ne.u32 p, %1, 0;\n@p mov.u32 %0, %%clock;\n}" : "+r"(ck) : "r"(never) : "memory");
}

template <int ACCUM>
__device__ __forceinline__ void wgmma_rs_n128(uint32_t (&d)[32], uint32_t a0, uint32_t a1, uint32_t a2, uint32_t a3, uint64_t descB) {
  if (ACCUM == 1) {
    asm volatile(
        "wgmma.mma_async.sync.aligned.m64n128k16.f16.f16.f16 "
        "{%0, %1, %2, %3, %4, %5, %6, %7, %8, %9, %10, %11, %12, %13, %14, %15, %16, %17, %18, %19, %20, %21, %22, %23, %24, %25, %26, %27, %28, %29, %30, %31}, "
        "{%32, %33, %34, %35}, %36, 1, 1, 1, 1;\n"
        : "+r"(d[0]), "+r"(d[1]), "+r"(d[2]), "+r"(d[3]), "+r"(d[4]), "+r"(d[5]), "+r"(d[6]), "+r"(d[7]), "+r"(d[8]), "+r"(d[9]), "+r"(d[10]), "+r"(d[11]), "+r"(d[12]), "+r"(d[13]), "+r"(d[14]), "+r"(d[15]), "+r"(d[16]), "+r"(d[17]), "+r"(d[18]), "+r"(d[19]), "+r"(d[20]), "+r"(d[21]), "+r"(d[22]), "+r"(d[23]), "+r"(d[24]), "+r"(d[25]), "+r"(d[26]), "+r"(d[27]), "+r"(d[28]), "+r"(d[29]), "+r"(d[30]), "+r"(d[31])
        : "r"(a0), "r"(a1), "r"(a2), "r"(a3), "l"(descB));
  }
  if (ACCUM == 0) {
    asm volatile(
        "wgmma.mma_async.sync.aligned.m64n128k16.f16.f16.f16 "
        "{%0, %1, %2, %3, %4, %5, %6, %7, %8, %9, %10, %11, %12, %13, %14, %15, %16, %17, %18, %19, %20, %21, %22, %23, %24, %25, %26, %27, %28, %29, %30, %31}, "
        "{%32, %33, %34, %35}, %36, 0, 1, 1, 1;\n"
        : "=r"(d[0]), "=r"(d[1]), "=r"(d[2]), "=r"(d[3]), "=r"(d[4]), "=r"(d[5]), "=r"(d[6]), "=r"(d[7]), "=r"(d[8]), "=r"(d[9]), "=r"(d[10]), "=r"(d[11]), "=r"(d[12]), "=r"(d[13]), "=r"(d[14]), "=r"(d[15]), "=r"(d[16]), "=r"(d[17]), "=r"(d[18]), "=r"(d[19]), "=r"(d[20]), "=r"(d[21]), "=r"(d[22]), "=r"(d[23]), "=r"(d[24]), "=r"(d[25]), "=r"(d[26]), "=r"(d[27]), "=r"(d[28]), "=r"(d[29]), "=r"(d[30]), "=r"(d[31])
        : "r"(a0), "r"(a1), "r"(a2), "r"(a3), "l"(descB));
  }
}
template <int ACCUM>
__device__ __forceinline__ void wgmma_rs_n96(uint32_t (&d)[24], uint32_t a0, uint32_t a1, uint32_t a2, uint32_t a3, uint64_t descB) {
  if (ACCUM == 1) {
    asm volatile(
        "wgmma.mma_async.sync.aligned.m64n96k16.f16.f16.f16 "
        "{%0, %1, %2, %3, %4, %5, %6, %7, %8, %9, %10, %11, %12, %13, %14, %15, %16, %17, %18, %19, %20, %21, %22, %23}, "
        "{%24, %25, %26, %27}, %28, 1, 1, 1, 1;\n"
        : "+r"(d[0]), "+r"(d[1]), "+r"(d[2]), "+r"(d[3]), "+r"(d[4]), "+r"(d[5]), "+r"(d[6]), "+r"(d[7]), "+r"(d[8]), "+r"(d[9]), "+r"(d[10]), "+r"(d[11]), "+r"(d[12]), "+r"(d[13]), "+r"(d[14]), "+r"(d[15]), "+r"(d[16]), "+r"(d[17]), "+r"(d[18]), "+r"(d[19]), "+r"(d[20]), "+r"(d[21]), "+r"(d[22]), "+r"(d[23])
        : "r"(a0), "r"(a1), "r"(a2), "r"(a3), "l"(descB));
  }
  if (ACCUM == 0) {
    asm volatile(
        "wgmma.mma_async.sync.aligned.m64n96k16.f16.f16.f16 "
        "{%0, %1, %2, %3, %4, %5, %6, %7, %8, %9, %10, %11, %12, %13, %14, %15, %16, %17, %18, %19, %20, %21, %22, %23}, "
        "{%24, %25, %26, %27}, %28, 0, 1, 1, 1;\n"
        : "=r"(d[0]), "=r"(d[1]), "=r"(d[2]), "=r"(d[3]), "=r"(d[4]), "=r"(d[5]), "=r"(d[6]), "=r"(d[7]), "=r"(d[8]), "=r"(d[9]), "=r"(d[10]), "=r"(d[11]), "=r"(d[12]), "=r"(d[13]), "=r"(d[14]), "=r"(d[15]), "=r"(d[16]), "=r"(d[17]), "=r"(d[18]), "=r"(d[19]), "=r"(d[20]), "=r"(d[21]), "=r"(d[22]), "=r"(d[23])
        : "r"(a0), "r"(a1), "r"(a2), "r"(a3), "l"(descB));
  }
}
template <int ACCUM>
__device__ __forceinline__ void wgmma_rs_n32(uint32_t (&d)[8], uint32_t a0, uint32_t a1, uint32_t a2, uint32_t a3, uint64_t descB) {
  if (ACCUM == 1) {
    asm volatile(
        "wgmma.mma_async.sync.aligned.m64n32k16.f16.f16.f16 "
        "{%0, %1, %2, %3, %4, %5, %6, %7}, "
        "{%8, %9, %10, %11}, %12, 1, 1, 1, 1;\n"
        : "+r"(d[0]), "+r"(d[1]), "+r"(d[2]), "+r"(d[3]), "+r"(d[4]), "+r"(d[5]), "+r"(d[6]), "+r"(d[7])
        : "r"(a0), "r"(a1), "r"(a2), "r"(a3), "l"(descB));
  }
  if (ACCUM == 0) {
    asm volatile(
        "wgmma.mma_async.sync.aligned.m64n32k16.f16.f16.f16 "
        "{%0, %1, %2, %3, %4, %5, %6, %7}, "
        "{%8, %9, %10, %11}, %12, 0, 1, 1, 1;\n"
        : "=r"(d[0]), "=r"(d[1]), "=r"(d[2]), "=r"(d[3]), "=r"(d[4]), "=r"(d[5]), "=r"(d[6]), "=r"(d[7])
        : "r"(a0), "r"(a1), "r"(a2), "r"(a3), "l"(descB));
  }
}

__device__ __forceinline__ float rbf(float x) { return __bfloat162float(__float2bfloat16_rn(x)); }
__device__ __forceinline__ float warp_sum(float v) {
#pragma unroll
  for (int o = 16; o > 0; o >>= 1) v += __shfl_xor_sync(0xffffffffu, v, o);
  return v;
}

__device__ __noinline__ void general_element(const int* __restrict__ idx, const __nv_bfloat16* __restrict__ table,
                                             const int* __restrict__ ii, const int* __restrict__ jj,
                                             const __nv_bfloat16* __restrict__ W, const __nv_bfloat16* __restrict__ bias,
                                             const __nv_bfloat16* __restrict__ hvec, const __nv_bfloat16* __restrict__ pvec,
                                             __nv_bfloat16* __restrict__ out, float* ev) {
  const int lane = threadIdx.x & 31;
  auto pair4 = [&](int p, float (&pr)[4]) {
    const __nv_bfloat16* a = table + (size_t)idx[ii[p]] * kD + 4 * lane;
    const __nv_bfloat16* b = table + (size_t)idx[jj[p]] * kD + 4 * lane;
#pragma unroll
    for (int q = 0; q < 4; q++) pr[q] = rbf(__bfloat162float(a[q]) * __bfloat162float(b[q]));
  };
  float m = -INFINITY;
  bool has_nan = false;
  for (int p = 0; p < kP; p++) {
    float pr[4], x[4] = {0.f, 0.f, 0.f, 0.f};
    pair4(p, pr);
    for (int l = 0; l < 32; l++) {
#pragma unroll
      for (int q = 0; q < 4; q++) {
        const float v = __shfl_sync(0xffffffffu, pr[q], l);
        const uint2 w = *reinterpret_cast<const uint2*>(W + (4 * l + q) * kD + 4 * lane);
        x[0] = fmaf(v, __uint_as_float(w.x << 16), x[0]);
        x[1] = fmaf(v, __uint_as_float(w.x & 0xffff0000u), x[1]);
        x[2] = fmaf(v, __uint_as_float(w.y << 16), x[2]);
        x[3] = fmaf(v, __uint_as_float(w.y & 0xffff0000u), x[3]);
      }
    }
    float e = 0.f;
#pragma unroll
    for (int q = 0; q < 4; q++) {
      const float y = rbf(rbf(x[q]) + __bfloat162float(bias[4 * lane + q]));
      e = fmaf(rbf(0.5f * rbf(y + fabsf(y))), __bfloat162float(hvec[4 * lane + q]), e);
    }
    e = rbf(warp_sum(e));
    has_nan |= (e != e);
    m = fmaxf(m, e);
    if (lane == 0) ev[p] = e;
  }
  __syncwarp();
  float l = 0.f;
  for (int p = lane; p < kP; p += 32) l += expf(ev[p] - m);
  l = warp_sum(l);
  float pooled[4] = {0.f, 0.f, 0.f, 0.f};
  for (int p = 0; p < kP; p++) {
    float pr[4];
    pair4(p, pr);
    const float al = rbf(expf(ev[p] - m) / l);
#pragma unroll
    for (int q = 0; q < 4; q++) pooled[q] = fmaf(al, pr[q], pooled[q]);
  }
  float o = 0.f;
#pragma unroll
  for (int q = 0; q < 4; q++) o = fmaf(rbf(pooled[q]), __bfloat162float(pvec[4 * lane + q]), o);
  o = warp_sum(o);
  if (has_nan) o = __int_as_float(0x7fffffff);
  if (lane == 0) *out = __float2bfloat16_rn(o);
}

__device__ __forceinline__ void helper_rest(const int* __restrict__ idx, const __nv_bfloat16* __restrict__ table,
                                            const __nv_bfloat16* __restrict__ W, const Late& late, int per, int n_elem,
                                            int n_left, uint8_t* smem) {
  constexpr uint32_t sbase = 0x400u;
  uint32_t tid, cta;
  asm volatile("mov.u32 %0, %%tid.x;\nmov.u32 %1, %%ctaid.x;" : "=r"(tid), "=r"(cta));
  const int t = tid & 127, lane = tid & 31, wq = (tid >> 5) & 3;
  cta -= n_left;
  const int b0 = cta * per, last_row = n_elem * kF - 2;
  const int n_out = min(per, n_elem - b0), n_c = max(n_out, 2);
  const int grp = 7 - (t >> 4);
  const bool v01 = grp < 7, v23 = grp < 6;
  int irow = (b0 + (n_c > 2 ? 2 : 0)) * kF + 4 * grp;
  uint2 gi01 = ldg64(idx + min(irow, last_row));
  uint2 gi23 = ldg64(idx + min(irow + 2, last_row));
  const __nv_bfloat16* gsrc = table + (t & 15) * 8;
  uint32_t cv_ptr = sbase + OFF_EMB + 2 * kElem + 4 * grp * kRow + (t & 15) * 16;
  uint32_t me = 0, ck = 0;
  auto track = [&](const uint4& a, const uint4& b, bool on) {
    const uint32_t m = babsmax2(babsmax2(babsmax2(a.x, a.y), babsmax2(a.z, a.w)), babsmax2(babsmax2(b.x, b.y), babsmax2(b.z, b.w)));
    me = babsmax2(me, on ? m : 0u);
  };
  named_bar_sync(6, 160);
#pragma unroll 1
  for (int e = 2; e < n_c + 2; e++) {
    const uint4 g0 = ldg_row(gsrc, gi01.x, v01), g1 = ldg_row(gsrc, gi01.y, v01);
    const uint4 g2 = ldg_row(gsrc, gi23.x, v23), g3 = ldg_row(gsrc, gi23.y, v23);
    irow += e + 1 == n_c ? (1 - n_c) * kF : kF;
    gi01 = ldg64(idx + min(irow, last_row));
    gi23 = ldg64(idx + min(irow + 2, last_row));
    uint4 h0 = convert(g0), h1 = convert(g1), h2 = convert(g2), h3 = convert(g3);
    asm volatile("" : "+r"(h0.x), "+r"(h0.y), "+r"(h0.z), "+r"(h0.w), "+r"(h1.x), "+r"(h1.y), "+r"(h1.z), "+r"(h1.w),
                      "+r"(h2.x), "+r"(h2.y), "+r"(h2.z), "+r"(h2.w), "+r"(h3.x), "+r"(h3.y), "+r"(h3.z), "+r"(h3.w));
    sched_fence(ck, tid >> 10);
    sts128p<0>(cv_ptr, h0, v01 && e < n_c);
    sts128p<kRow>(cv_ptr, h1, v01 && e < n_c);
    sts128p<2 * kRow>(cv_ptr, h2, v23 && e < n_c);
    sts128p<3 * kRow>(cv_ptr, h3, v23 && e < n_c);
    __syncwarp();
    mbar_arrive_p(sbase + OFF_BAR + 8 * e, lane == 0 && e < n_c);
    sched_fence(ck, tid >> 10);
    cv_ptr += kElem;
    track(g0, g1, v01);
    track(g2, g3, v23);
  }
  bool ok_cta;
  float ds;
  {
    const uint32_t s0 = ldg32(late.vec[t >> 6] + 2 * (t & 63)), s1 = ldg32(late.vec[2] + 2 * (t & 63));
    const uint32_t s2 = ldg32(late.vec[(t >> 6) ^ 1] + 2 * (t & 63));
    uint32_t pi[3], pj[3];
#pragma unroll
    for (int r = 0; r < 3; r++) {
      pi[r] = ldg32(late.ii + min(t + 128 * r, kP - 1));
      pj[r] = ldg32(late.jj + min(t + 128 * r, kP - 1));
    }
    float v0 = 16.f * (fabsf(__uint_as_float(s0 << 16)) + fabsf(__uint_as_float(s0 & 0xffff0000u)));
    float v1 = 16.f * (fabsf(__uint_as_float(s1 << 16)) + fabsf(__uint_as_float(s1 & 0xffff0000u)));
    if (t >= 64) v1 = fabsf(__uint_as_float(s0 << 16) * __uint_as_float(s2 << 16)) +
                      fabsf(__uint_as_float(s0 & 0xffff0000u) * __uint_as_float(s2 & 0xffff0000u));
    bool good = true;
#pragma unroll
    for (int r = 0; r < 3; r++)
      good &= (pi[r] < pj[r]) & (pj[r] < kF) & (((pi[r] * (2 * kF - 1 - pi[r])) >> 1) + pj[r] - pi[r] - 1 == min(t + 128 * r, kP - 1));
    if (!good) v0 = __int_as_float(0x7fffffff);
    v0 = warp_sum(v0);
    v1 = warp_sum(v1);
    sts32p(sbase + OFF_STAT + 64 + wq * 4, __float_as_uint(v0), lane == 0);
    sts32p(sbase + OFF_STAT + 80 + wq * 4, __float_as_uint(v1), lane == 0);
    sts32p(sbase + OFF_STAT + 16 + wq * 4 + ck, redux_max(absmax_bits(me)), lane == 0);
    named_bar_sync(6, 128);
    const uint32_t st = lds32(sbase + OFF_STAT + lane * 4);
    const float Wm = 2048.f * __uint_as_float(redux_max(lane < 4 ? st : 0u) << 16);
    const float M = __uint_as_float(redux_max(lane >= 4 && lane < 8 ? st : 0u) << 16);
    const float sp = __uint_as_float(st) + __shfl_xor_sync(0xffffffffu, __uint_as_float(st), 1);
    const float Bs = __shfl_sync(0xffffffffu, sp, 16);
    const float Hs = __shfl_sync(0xffffffffu, sp, 18);
    const float Ps = __shfl_sync(0xffffffffu, sp, 20);
    const float HB = __shfl_sync(0xffffffffu, sp, 22);
    const float M2 = M * M, X = fmaf(M2, Wm, Bs), G = fmaf(2.f, M, 1.f);
    constexpr float u = 1.f / 33554432.f;
    const float de = u * (Hs * (Wm * G + 128.f * M2 + 16.f) + 128.f * X + 256.f);
    ds = u * (Ps * G + 128.f * M2 + 256.f);
    ok_cta = M2 <= 60000.f && Wm <= 128.f * 60000.f && X <= 60000.f && Hs <= 60000.f && Ps <= 60000.f && de <= 1.f && HB <= 64.f;
  }
#pragma unroll 1
  for (int e = wq; e < n_c; e += 4) {
    const uint32_t ea = sbase + OFF_ES + (2 + e) * ES_STRIDE + lane * 16;
    float l = 0.f, a = 0.f;
    if (lane == 0 && e < n_out) {
      float2* const gp = g_left + b0 + e;
      for (uint32_t it = 0; it < (1u << 22); it++) {
        asm volatile("{\n.reg .b64 v;\nld.volatile.global.b64 v, [%2];\nmov.b64 {%0,%1}, v;\n}" : "=f"(l), "=f"(a) : "l"(gp) : "memory");
        if (__float_as_uint(l) != 0u) break;
        __nanosleep(200);
      }
      asm volatile("st.volatile.global.b64 [%0], %1;" ::"l"(gp), "l"(0ull) : "memory");
    }
    __syncwarp();
    uint32_t mx = lane == 0 && !(l > 0.f) ? 0x7fffu : 0u;
    auto take = [&](const uint4& v) {
      const uint32_t es = hadd2(hadd2(v.x, v.y), hadd2(v.z, v.w));
      const float w = exp_e(es);
      mx = habsmax2(mx, es);
      l += w;
      a = fmaf(w, h_hi(es), a);
    };
    const bool last = e + 2 >= n_c;
    if (last) named_bar_sync(13 + (e & 1), 160);
    else mbar_wait(sbase + OFF_BAR + 80 + 8 * e, 0);
    {
      uint4 v[6];
      static_for<0, 6>([&](auto Qc) { v[decltype(Qc)::value] = lds128<decltype(Qc)::value * 512>(ea); });
      sched_fence(ck, tid >> 10);
#pragma unroll
      for (int q = 0; q < 6; q++) take(v[q]);
    }
    __nv_bfloat16* op = late.out + b0 + e;
    asm volatile("" : "+l"(op));
    if (last) named_bar_sync(10 + (e & 1), 160);
    take(lds128<3072>(ea));
    take(lds128<3072 + 512>(ea));
    asm volatile("" : "+f"(l), "+f"(a), "+r"(mx));
    sched_fence(ck, tid >> 10);
    asm volatile("{\n.reg .pred p, q;\nsetp.ne.u32 q, %1, 0;\nsetp.eq.and.u32 p|q, %0, 0, q;\n@p bar.sync 8, 160;\n@q bar.sync 9, 160;\n}"
                 ::"r"(e & 1), "r"((uint32_t)last) : "memory");
    {
      const uint4 v0 = lds128<4096>(ea + ck), v1 = lds128<4096 + 512>(ea);
      take(v0);
      take(v1);
    }
    const uint32_t big = __ballot_sync(0xffffffffu, ds <= fabsf(h_hi(mx)) * (1.f / 16384.f));
    const uint32_t bad = __ballot_sync(0xffffffffu, ((mx & 0x7fffu) > 0x7000u) | ((mx & 0x7c000000u) == 0x7c000000u));
    const bool ok = (big != 0u) & (bad == 0u) & ok_cta;
#pragma unroll
    for (int o = 0; o < 5; o++) {
      l += __uint_as_float(shfl_xor_v(__float_as_uint(l), 1 << o));
      a += __uint_as_float(shfl_xor_v(__float_as_uint(a), 1 << o));
    }
    float r;
    asm("rcp.approx.ftz.f32 %0, %1;" : "=f"(r) : "f"(l));
    if (lane == 0 && e < n_out) *op = __float2bfloat16_rn(a * 0.0625f * r);
    if (!ok && e < n_out)
      general_element(idx + (b0 + e) * kF, table, late.ii, late.jj, W, late.vec[0], late.vec[1], late.vec[2], op, reinterpret_cast<float*>(smem + OFF_EMB + e * kElem));
  }
}

__global__ void __launch_bounds__(kThreads, 1)
afm_kernel(const int* __restrict__ idx, const __nv_bfloat16* __restrict__ table, const __nv_bfloat16* __restrict__ W,
           uint32_t ix_stride, uint32_t ix_bias, uint32_t ix_last, int per, int n_elem, int n_left,
           const __grid_constant__ Late late) {
  extern __shared__ __align__(1024) uint8_t smem[];
  constexpr uint32_t sbase = 0x400u;

  const int tid = threadIdx.x;
  const int t = tid & 127;
  const int lane = tid & 31;
  const int warp = tid >> 5;
  uint32_t ck = 0;
  uint32_t never = tid >> 10;
  const int grp = 7 - (t >> 4);
  const bool v01 = grp < 7, v23 = grp < 6;
  const bool is_left = (int)blockIdx.x < n_left;
  const uint32_t ioff = blockIdx.x * ix_stride - ix_bias + ((tid >> 7) * kF + 4 * grp) * 4;
  uint2 gi01, gi23;
  ldg_idx4(gi01, gi23, idx, ioff <= ix_last ? ioff : 0u, v01 && tid < 256, v23 && tid < 256);
  asm volatile("{\n.reg .pred p;\nsetp.ge.u32 p, %1, %2;\n@p prefetch.global.L2 [%0];\n}" ::"l"(W + ((blockIdx.x * 32 + tid) & 255) * 64), "r"(tid), "n"(384 - 32) : "memory");
  sched_fence(ck, never);
  const int wq = warp & 3;
  const int wg = __shfl_sync(0xffffffffu, tid >> 7, 0);
  const int n_c = max(min(per, n_elem - ((int)blockIdx.x - n_left) * per), 2);
  const __nv_bfloat16* gsrc = table + (t & 15) * 8;
  asm volatile("" : "+l"(gsrc));
  uint32_t cv_ptr = sbase + OFF_EMB + wg * kElem + 4 * grp * kRow + (t & 15) * 16;

  if (wg < 2) {
    const int c = lane & 3;
    const int tau = t >> 2;
    if (wg == 0) {
      asm volatile("cp.async.ca.shared.global [%0], [%1], 4;\ncp.async.ca.shared.global [%0+4], [%2], 4;\ncp.async.commit_group;"
                   ::"r"(sbase + OFF_ES + t * 8), "l"(late.vec[t >> 6] + 2 * (t & 63)), "l"(late.vec[2] + 2 * (t & 63)) : "memory");
    }
    const int nb = (n_c - wg + 1) >> 1;
    const uint32_t sc = late.sched.e[tau];
    uint4 g0[4];
    const bool q01 = v01 && !is_left, q23 = v23 && !is_left;
    sched_fence(ck, never);
    if (wg == 1) {
      uint32_t y;
      asm volatile("or.b32 %0, %1, %2;" : "=r"(y) : "r"(gi01.x), "r"(gi23.x));
      const uint32_t t0 = clock32() + (y >> 31);
      while (clock32() - t0 < 450) {
      }
    }
    sched_fence(ck, never);
    g0[0] = ldg_row(gsrc, gi01.x, q01);
    g0[1] = ldg_row(gsrc, gi01.y, q01);
    g0[2] = ldg_row(gsrc, gi23.x, q23);
    g0[3] = ldg_row(gsrc, gi23.y, q23);
    sched_fence(ck, never);
    const int* lip = idx + min((int)(blockIdx.x * 256 + tau * 8 + wg), n_elem - 1) * kF;
    const uint2 li01 = ldg64p(lip, is_left), li23 = ldg64p(lip + 2, is_left);
    if (warp == 0) {
      if (lane == 0) {
#pragma unroll
        for (int i = 0; i < 16; i++) mbar_init(sbase + OFF_BAR + 8 * i, i < 2 ? 1 : i < 8 ? 4 : 128);
        mbar_arrive(sbase + OFF_BAR);
        mbar_arrive(sbase + OFF_BAR + 8);
      }
      if (smem_u32(smem) != sbase) __trap();
      __syncwarp();
      named_bar_arrive(6, 160);
    }
    if (wg == 0) {
      asm volatile("cp.async.wait_group 0;" ::: "memory");
      const uint32_t s0 = lds32(sbase + OFF_ES + t * 8), s1 = lds32(sbase + OFF_ES + t * 8 + 4);
      sts32(sbase + OFF_VEC + ((t & 112u) | ((t & 3u) << 2) | ((t >> 2) & 3u)) * 4,
            bf2h_x16(s0) ^ (t < 64 ? 0x80008000u : 0u));
      sts32(sbase + OFF_VEC + 512 + (t & 63) * 4, bf2h_x16(s1));
      named_bar_arrive(12, 256);
    }
    asm volatile("{\n.reg .pred p;\nsetp.eq.u32 p, %0, 0;\n@p bar.sync 1, 128;\n@!p bar.sync 12, 256;\n}" ::"r"(wg) : "memory");
    sched_fence(ck, never);
    uint32_t bs[16], hs[16], ps[16];
    load_vec(ps, sbase + OFF_VEC + 512 + c * 16);
    load_vec(bs, sbase + OFF_VEC + c * 16);
    load_vec(hs, sbase + OFF_VEC + 256 + c * 16);
    sched_fence(ck, never);
    if (wg == 1) named_bar_sync(7, 256);
    asm volatile("setmaxnreg.inc.sync.aligned.u32 %0;" ::"n"(216));
    if (wg == 0) named_bar_arrive(7, 256);
    uint32_t pt_ptr = shfl_xor<0>(sbase + OFF_ES + (2 + wg) * ES_STRIDE + t * 4);
    never = pt_ptr >> 31;
    uint32_t ra[6];
#pragma unroll
    for (int r = 0; r < 6; r++) ra[r] = sbase + OFF_EMB + wg * kElem + c * 16 + ((sc >> (5 * r)) & 31u) * kRow;
    asm volatile("" : "+r"(ra[0]), "+r"(ra[1]), "+r"(ra[2]), "+r"(ra[3]), "+r"(ra[4]), "+r"(ra[5]));
    sched_fence(ck, never);
    uint32_t Af[32], acc[32], S0[16], S1[16], S2[16], S3[16];
    constexpr uint64_t dB = (uint64_t)(((sbase + OFF_B) & 0x3FFFFu) >> 4) | ((uint64_t)(B_NBLK >> 4) << 16) |
                            ((uint64_t)(1024 >> 4) << 32) | ((uint64_t)1 << 62);
    auto products = [&](const uint32_t (&X)[16], const uint32_t (&Y)[16], const uint32_t (&Z)[16]) {
#pragma unroll
      for (int i = 0; i < 16; i++) {
        Af[2 * i] = hmul2(X[i], Z[i]);
        Af[2 * i + 1] = hmul2(Y[i], Z[i]);
      }
    };
    auto mma_tile = [&]() {
      fence_regs(Af);
      wgmma_fence();
#pragma unroll
      for (int s = 0; s < 8; s++) {
        const uint64_t d = dB + (uint64_t)(s * (2048 >> 4));
        if (s == 0) wgmma_rs_n128<0>(acc, Af[0], Af[1], Af[2], Af[3], d);
        else wgmma_rs_n128<1>(acc, Af[4 * s], Af[4 * s + 1], Af[4 * s + 2], Af[4 * s + 3], d);
      }
      wgmma_commit();
    };
    auto issue = [&]() {
      mma_tile();
      bar_arrive2<5, 4>(wg);
    };
    uint32_t eh0 = 0, eh1 = 0, sh0 = 0, sh1 = 0;
    auto fold = [&]() {
      eh0 = hadd2(__byte_perm(eh0, sh0, 0x5410), __byte_perm(eh0, sh0, 0x7632));
      eh1 = hadd2(__byte_perm(eh1, sh1, 0x5410), __byte_perm(eh1, sh1, 0x7632));
    };
    auto s_chain = [&]() {
      sh0 = hmul2(Af[0], ps[0]);
      sh1 = hmul2(Af[1], ps[0]);
#pragma unroll
      for (int i = 1; i < 16; i++) {
        sh0 = hfma2(Af[2 * i], ps[i], sh0);
        sh1 = hfma2(Af[2 * i + 1], ps[i], sh1);
      }
      asm volatile("" : "+r"(sh0), "+r"(sh1)::"memory");
    };
    auto epilogue = [&]() {
      wgmma_wait<0>();
      fence_regs(acc);
      fence_regs(S0); fence_regs(S1); fence_regs(S2); fence_regs(S3);
      eh0 = hmul2(bias_relu2(acc[0], bs[0]), hs[0]);
      eh1 = hmul2(bias_relu2(acc[1], bs[0]), hs[0]);
#pragma unroll
      for (int i = 1; i < 16; i++) {
        eh0 = hfma2(bias_relu2(acc[2 * i], bs[i]), hs[i], eh0);
        eh1 = hfma2(bias_relu2(acc[2 * i + 1], bs[i]), hs[i], eh1);
      }
      asm volatile("" : "+r"(eh0), "+r"(eh1)::"memory");
    };
    if (is_left) {
      if (wg == 1) named_bar_arrive(4, 256);
      const int e0 = shfl_xor<0>(blockIdx.x * 256 + tau * 8 + wg);
      const __nv_bfloat16* lsrc = table + c * 8;
      uint32_t ia, ib, ic, id, ma;
      float lsum = 0.f, asum = 0.f;
      auto load_ix = [&](int r) {
        const int* ip = idx + min(e0 + 2 * r, n_elem - 1) * kF;
        const uint2 x = ldg64(ip), y = ldg64(ip + 2);
        ia = x.x; ib = x.y; ic = y.x; id = y.y;
      };
      auto load_row = [&](uint32_t (&v)[16], uint32_t row) {
#pragma unroll
        for (int kb = 0; kb < 4; kb++) {
          const uint4 x = ldg_row(lsrc + 32 * kb, row, true);
          v[4 * kb] = x.x; v[4 * kb + 1] = x.y; v[4 * kb + 2] = x.z; v[4 * kb + 3] = x.w;
        }
      };
      auto cvt_row = [&](uint32_t (&v)[16]) {
#pragma unroll
        for (int i = 0; i < 16; i++) v[i] = bf2h(v[i]);
      };
      auto finish = [&](bool one_row) {
        s_chain();
        sched_fence(ck, never);
        epilogue();
        fold();
        uint32_t es = hadd2((c & 1) ? eh1 : eh0, shfl_xor<1>((c & 1) ? eh0 : eh1));
        es = hadd2(es, shfl_xor<2>(es));
        const float w = one_row && (c & 1) ? 0.f : exp_e(es);
        ma = habsmax2(ma, es);
        lsum += w;
        asum = fmaf(w, h_hi(es), asum);
        sched_fence(ck, never);
      };
      ia = li01.x; ib = li01.y; ic = li23.x; id = li23.y;
      load_row(S0, ia); load_row(S1, ib); load_row(S2, ic); load_row(S3, id);
      if (wg == 0) named_bar_sync(3, 256);
#pragma unroll 1
      for (int r = 0; r < 4; r++) {
        const int e = e0 + 2 * r;
        load_ix(r + 1);
        lsum = 0.f; asum = 0.f; ma = 0;
        cvt_row(S0); cvt_row(S1);
        products(S0, S0, S1);
        bar_sync2<4, 5>(wg);
        issue();
        cvt_row(S2); cvt_row(S3);
        finish(true);
        products(S0, S1, S2);
        bar_sync2<4, 5>(wg);
        issue();
        load_row(S2, ic);
        finish(false);
        products(S0, S1, S3);
        bar_sync2<4, 5>(wg);
        issue();
        load_row(S0, ia); load_row(S1, ib); load_row(S3, id);
        finish(false);
        lsum += __shfl_xor_sync(0xffffffffu, lsum, 1);
        asum += __shfl_xor_sync(0xffffffffu, asum, 1);
        ma = habsmax2(ma, shfl_xor<1>(ma));
        if ((ma & 0x7fffu) > 0x7000u || ((ma >> 16) & 0x7fffu) >= 0x7c00u) lsum = __int_as_float(0x7fffffff);
        if (c == 0 && e < n_elem)
          asm volatile("{\n.reg .b64 v;\nmov.b64 v, {%1,%2};\nst.volatile.global.b64 [%0], v;\n}" ::"l"(g_left + e + ck), "f"(lsum), "f"(asum) : "memory");
      }
      if (wg == 0) named_bar_sync(4, 256);
      return;
    }
    sts128p<0>(cv_ptr, convert_f(g0[0]), v01);
    sts128p<kRow>(cv_ptr, convert_f(g0[1]), v01);
    sts128p<2 * kRow>(cv_ptr, convert_f(g0[2]), v23);
    sts128p<3 * kRow>(cv_ptr, convert_f(g0[3]), v23);
    asm volatile("{\n.reg .pred p;\nsetp.eq.u32 p, %0, 0;\n@p bar.sync 3, 256;\n@!p bar.sync 2, 128;\n}" ::"r"(wg) : "memory");

    static_for<0, 4>([&](auto Kc) {
      constexpr int kb = decltype(Kc)::value;
      const uint4 z = lds128<64 * kb>(ra[5]), x = lds128<64 * kb>(ra[0]), y = lds128<64 * kb>(ra[1]);
      S3[4 * kb] = z.x; S3[4 * kb + 1] = z.y; S3[4 * kb + 2] = z.z; S3[4 * kb + 3] = z.w;
      S0[4 * kb] = x.x; S0[4 * kb + 1] = x.y; S0[4 * kb + 2] = x.z; S0[4 * kb + 3] = x.w;
      S1[4 * kb] = y.x; S1[4 * kb + 1] = y.y; S1[4 * kb + 2] = y.z; S1[4 * kb + 3] = y.w;
      if (kb & 1) sched_fence(ck, never);
    });
#pragma unroll
    for (int i = 0; i < 16; i++) S2[i] = 0;
    static_for<0, 2>([&](auto Hc) {
      constexpr int h = decltype(Hc)::value, n = 16 / 2;
#pragma unroll
      for (int i = h * n; i < h * n + n; i++) {
        Af[2 * i] = hmul2(S0[i], S3[i]);
        Af[2 * i + 1] = hmul2(S1[i], S3[i]);
        asm volatile("" : "+r"(Af[2 * i]), "+r"(Af[2 * i + 1])::"memory");
      }
      if (h == 0) {
        if (wg == 1) named_bar_sync(5, 256);
        sched_fence(ck, never);
      }
      wgmma_fence();
#pragma unroll
      for (int s = h * n / 2; s < (h * n + n) / 2; s++) {
        const uint64_t d = dB + (uint64_t)(s * (2048 >> 4));
        if (s == 0) wgmma_rs_n128<0>(acc, Af[0], Af[1], Af[2], Af[3], d);
        else wgmma_rs_n128<1>(acc, Af[4 * s], Af[4 * s + 1], Af[4 * s + 2], Af[4 * s + 3], d);
      }
      sched_fence(ck, never);
    });
    wgmma_commit();
    bar_arrive2<5, 4>(wg);
    sched_fence(ck, never);

    auto bump = [&](uint32_t& r) { asm volatile("add.u32 %0, %0, %1;" : "+r"(r) : "n"(2 * kElem)); };
    int left = nb - 1;
    ra[0] += 2 * kElem; ra[1] += 2 * kElem; ra[5] += 2 * kElem;
    uint4 r0, r1;
    uint32_t el = wg, rdy = 0;
    auto tile = [&](auto Tc) {
      constexpr int tt = decltype(Tc)::value & 7;
      constexpr bool last = decltype(Tc)::value > 7;
      sched_fence(ck, never);
      fold();
      const uint32_t f0 = eh0, f1 = eh1;
      sts32o<(tt == 0 ? 4096 - 2 * ES_STRIDE : (tt - 1) * 1024)>(pt_ptr, eh0);
      sts32o<(tt == 0 ? 4096 - 2 * ES_STRIDE : (tt - 1) * 1024) + 512>(pt_ptr, eh1);
      if (tt == 0) mbar_arrive(sbase + OFF_BAR + 64 + 8 * el);
      if (last) bar_arrive2<13, 14, 160>(wg);
      if (tt == 2) rdy = mbar_test(sbase + OFF_BAR + 8 * min(el + 2, n_c - 1), 0);
      sched_fence(ck, never);
      if (tt == 0) load_vec(S0, ra[3]);
      if (tt == 1) load_vec(S2, ra[4]);
      if (tt == 2) load_vec(S1, ra[2]);
      if (tt == 3 && !last) {
        load_vec(S0, ra[0]);
        r0 = lds128<0>(ra[1]);
        r1 = lds128<64>(ra[1]);
      }
      if (tt == 4) {
        load_vec(S3, ra[5]);
        const uint4 v2 = lds128<128>(ra[1]), v3 = lds128<192>(ra[1]);
        S1[8] = v2.x; S1[9] = v2.y; S1[10] = v2.z; S1[11] = v2.w; S1[12] = v3.x; S1[13] = v3.y; S1[14] = v3.z; S1[15] = v3.w;
        S1[0] = r0.x; S1[1] = r0.y; S1[2] = r0.z; S1[3] = r0.w; S1[4] = r1.x; S1[5] = r1.y; S1[6] = r1.z; S1[7] = r1.w;
      }
      sched_fence(ck, never);
      s_chain();
      sched_fence(ck, never);
      epilogue();
      sched_fence(ck, never);
      if (tt == 2 && !rdy) mbar_wait(sbase + OFF_BAR + 8 * min(el + 2, n_c - 1), 0);
      if (tt == 0) { products(S1, S3, S0); bump(ra[3]); }
      if (tt == 1) { products(S1, S0, S2); bump(ra[4]); }
      if (tt == 2) { products(S0, S2, S1); bump(ra[2]); }
      if (tt == 3) products(S1, S2, S3);
      if (tt == 4) {
        products(S0, S1, S3);
        bump(ra[0]); bump(ra[1]); bump(ra[5]);
        asm volatile("add.u32 %0, %0, %1;" : "+r"(pt_ptr) : "n"(2 * ES_STRIDE));
        el += 2;
      }
      sched_fence(ck, never);
      keep2(ck, f0, f1, never);
      if (!last) {
        bar_sync2<4, 5>(wg);
        issue();
      }
    };
#pragma unroll 1
    for (;;) {
      tile(std::integral_constant<int, 0>{});
      tile(std::integral_constant<int, 1>{});
      tile(std::integral_constant<int, 2>{});
      if (left == 0) break;
      tile(std::integral_constant<int, 3>{});
      tile(std::integral_constant<int, 4>{});
      left--;
    }
    tile(std::integral_constant<int, 8 + 3>{});
    auto side = [&]() {
      fold();
      sts32o<3072>(pt_ptr, eh0);
      sts32o<3072 + 512>(pt_ptr, eh1);
      bar_arrive2<10, 11, 160>(wg);
      s_chain();
    };
    bar_sync2<4, 5>(wg);
    uint32_t al[96 / 4], ah[32 / 4];
    fence_regs(Af);
    wgmma_fence();
#pragma unroll
    for (int s = 0; s < 8; s++) {
      const uint64_t d = dB + (uint64_t)(s * (2048 >> 4));
      if (s == 0) wgmma_rs_n96<0>(al, Af[0], Af[1], Af[2], Af[3], d);
      else wgmma_rs_n96<1>(al, Af[4 * s], Af[4 * s + 1], Af[4 * s + 2], Af[4 * s + 3], d);
    }
    wgmma_commit();
    sched_fence(ck, never);
    side();
    sched_fence(ck, never);
    wgmma_fence();
#pragma unroll
    for (int s = 0; s < 8; s++) {
      const uint64_t d = dB + (uint64_t)(s * (2048 >> 4) + ((B_NBLK + (96 - 64) * 2) >> 4));
      if (s == 0) wgmma_rs_n32<0>(ah, Af[0], Af[1], Af[2], Af[3], d);
      else wgmma_rs_n32<1>(ah, Af[4 * s], Af[4 * s + 1], Af[4 * s + 2], Af[4 * s + 3], d);
    }
    wgmma_commit();
    bar_arrive2<5, 4>(wg);
    wgmma_wait<1>();
    fence_regs(al);
    eh0 = hmul2(bias_relu2(al[0], bs[0]), hs[0]);
    eh1 = hmul2(bias_relu2(al[1], bs[0]), hs[0]);
#pragma unroll
    for (int i = 1; i < 96 / 8; i++) {
      eh0 = hfma2(bias_relu2(al[2 * i], bs[i]), hs[i], eh0);
      eh1 = hfma2(bias_relu2(al[2 * i + 1], bs[i]), hs[i], eh1);
    }
    asm volatile("" : "+r"(eh0), "+r"(eh1)::"memory");
    sched_fence(ck, never);
    wgmma_wait<0>();
    fence_regs(ah);
#pragma unroll
    for (int i = 0; i < 32 / 8; i++) {
      eh0 = hfma2(bias_relu2(ah[2 * i], bs[96 / 8 + i]), hs[96 / 8 + i], eh0);
      eh1 = hfma2(bias_relu2(ah[2 * i + 1], bs[96 / 8 + i]), hs[96 / 8 + i], eh1);
    }
    fold();
    sts32o<4096>(pt_ptr + ck, eh0);
    sts32o<4096 + 512>(pt_ptr, eh1);
    bar_arrive2<8, 9, 160>(wg);
    sched_fence(ck, never);
    if (wg == 0) {
      named_bar_sync(4, 256);
    } else if (n_c & 1) {
      for (int i = 0; i < 5; i++) {
        named_bar_sync(5, 256);
        named_bar_arrive(4, 256);
      }
    }
  } else {
    {
      asm volatile("setmaxnreg.dec.sync.aligned.u32 104;");
      uint4 wr[16];
#pragma unroll
      for (int r = 0; r < 16; r++) wr[r] = ldg128(W + (32 * wq + 2 * r) * kD + 8 * lane);
      const uint32_t wa = sbase + OFF_B + ((lane >> 3) & 1) * B_NBLK + wq * 4096 + (lane >> 4) * 128;
      const uint32_t lx = (lane & 7) ^ (lane >> 4);
      uint32_t wad[4], mw = 0;
#pragma unroll
      for (int x = 0; x < 4; x++) wad[x] = wa + ((lx ^ (2 * x)) << 4);
      sched_fence(ck, never);
      static_for<0, 16>([&](auto Rc) {
        constexpr int r = decltype(Rc)::value;
        uint4 v;
        v.x = bf2h_x16(wr[r].x); v.y = bf2h_x16(wr[r].y); v.z = bf2h_x16(wr[r].z); v.w = bf2h_x16(wr[r].w);
        sts128<(r & 3) * 1024 + (r >> 2) * 256>(wad[r >> 2], v);
        mw = babsmax2(babsmax2(mw, wr[r].x), babsmax2(wr[r].y, babsmax2(wr[r].z, wr[r].w)));
        if (r == 3) sched_fence(ck, never);
        if (r == 7 || r == 11) sched_fence(ck, never);
      });
      sched_fence(ck, never);
      fence_proxy_async();
      named_bar_arrive(3, 256);
      sched_fence(ck, never);
      sts32p(sbase + OFF_STAT + wq * 4 + ck, redux_max(absmax_bits(mw)), lane == 0);
    }
    named_bar_sync(15, 128);
    asm volatile("setmaxnreg.dec.sync.aligned.u32 %0;" ::"n"(504 - 2 * 216));
    if ((int)blockIdx.x >= n_left) helper_rest(idx, table, W, late, per, n_elem, n_left, smem);
    else {
      named_bar_sync(6, 160);
#pragma unroll 1
      for (int q = 2; q < 8; q++) {
        const int e = min((int)blockIdx.x * 256 + (t >> 2) * 8 + q, n_elem - 1);
        const uint32_t row = ldg32(idx + e * kF + (t & 3));
        asm volatile("prefetch.global.L2 [%0];\nprefetch.global.L2 [%0+128];" ::"l"(table + (size_t)row * kD) : "memory");
      }
    }
  }
}

}

extern "C" void kernel_launch(void* const* d_in, const int* in_sizes, int n_in, void* d_out, int out_size) {
  const int* idx = (const int*)d_in[0];
  const __nv_bfloat16* table = (const __nv_bfloat16*)d_in[1];
  const int* ii = (const int*)d_in[2];
  const int* jj = (const int*)d_in[3];
  const __nv_bfloat16* W = (const __nv_bfloat16*)d_in[4];
  const __nv_bfloat16* bias = (const __nv_bfloat16*)d_in[5];
  const __nv_bfloat16* hvec = (const __nv_bfloat16*)d_in[6];
  const __nv_bfloat16* pvec = (const __nv_bfloat16*)d_in[7];
  __nv_bfloat16* out = (__nv_bfloat16*)d_out;
  const int B = out_size;

  static int num_sms = 0;
  if (num_sms == 0) {
    int dev = 0;
    cudaGetDevice(&dev);
    cudaDeviceGetAttribute(&num_sms, cudaDevAttrMultiProcessorCount, dev);
    cudaFuncSetAttribute(afm_kernel, cudaFuncAttributeMaxDynamicSharedMemorySize, SMEM_BYTES);
  }
  const Sched sched = {{
    0x2d2cb011u, 0x2c9a0662u, 0x2876c228u, 0x26074141u, 0x2655c878u, 0x2985dc43u, 0x18722403u, 0x22299aaeu,
    0x02a6b0b1u, 0x30d73d00u, 0x00941af1u, 0x2ee29c4au, 0x2ad5a410u, 0x21250923u, 0x328a84aeu, 0x0d780599u,
    0x324551f8u, 0x3112a583u, 0x062ca4eeu, 0x155360e3u, 0x1cb204d6u, 0x1f4280c9u, 0x2776e487u, 0x090b60a2u,
    0x2413bf17u, 0x168b28ecu, 0x10c78a70u, 0x2f578ed1u, 0x1a334ac2u, 0x0888c875u, 0x1d5a3249u, 0x2305bf2au
  }};
  for (int off = 0; off < B; off += kMaxChunk) {
    const int n = B - off < kMaxChunk ? B - off : kMaxChunk;
    const int n_left = (n + 255) / 256;
    const int room = num_sms - n_left > 1 ? num_sms - n_left : 1;
    int per = (n + room - 1) / room;
    if (per > kMaxB) per = kMaxB;
    const int n_main = (n + per - 1) / per;
    const Late late = {{bias, hvec, pvec, pvec}, ii, jj, out + off, sched};
    afm_kernel<<<n_left + n_main, kThreads, SMEM_BYTES>>>(idx + (size_t)off * kF, table, W, per * kF * 4, n_left * per * kF * 4,
                                                          (n * kF - 2) * 4, per, n, n_left, late);
  }
}
```

```cpp
#include <cuda_runtime.h>
#include <cuda_bf16.h>
#include <cuda_fp16.h>
#include <stdint.h>
#include <type_traits>

namespace {

constexpr int kF = 26;
constexpr int kD = 128;
constexpr int kP = 325;
constexpr int kMaxB = 8;
constexpr int kThreads = 384;
constexpr int kRow = 320;
constexpr int kElem = kF * kRow;

constexpr int B_NBLK = 16 * 1024;
constexpr int OFF_B = 0;
constexpr int OFF_EMB = 2 * B_NBLK;
constexpr int OFF_ES = OFF_EMB + kMaxB * kElem;
constexpr int ES_STRIDE = 5 * 1024;
constexpr int OFF_VEC = OFF_ES + (kMaxB + 2) * ES_STRIDE;
constexpr int OFF_STAT = OFF_VEC + 768;
constexpr int OFF_BAR = OFF_STAT + 128;
constexpr int SMEM_USED = OFF_BAR + 128;
static_assert(OFF_EMB + (kMaxB + 2) * kElem <= SMEM_USED, "unused operand prefetches run up to 2 elements past the end");
constexpr int SMEM_BYTES = SMEM_USED;
static_assert(OFF_ES % 16 == 0 && OFF_VEC % 16 == 0 && OFF_STAT % 16 == 0 && kElem % 128 == 0, "alignment");

struct Sched { uint32_t e[32]; };
struct Late {
  const __nv_bfloat16* vec[4];
  const int* ii;
  const int* jj;
  __nv_bfloat16* out;
  Sched sched;
};

constexpr int kMaxChunk = 8192;
__device__ float2 g_left[kMaxChunk];

__device__ __forceinline__ uint32_t smem_u32(const void* p) { return (uint32_t)__cvta_generic_to_shared(p); }
__device__ __forceinline__ void named_bar_sync(int id, int n) { asm volatile("bar.sync %0, %1;" ::"r"(id), "r"(n) : "memory"); }
__device__ __forceinline__ void named_bar_arrive(int id, int n) { asm volatile("bar.arrive %0, %1;" ::"r"(id), "r"(n) : "memory"); }
template <int A, int B>
__device__ __forceinline__ void bar_sync2(uint32_t sel) {
  asm volatile("{\n.reg .pred p;\nsetp.eq.u32 p, %0, 0;\n@p bar.sync %1, 256;\n@!p bar.sync %2, 256;\n}" ::"r"(sel), "n"(A), "n"(B) : "memory");
}
template <int A, int B, int N = 256>
__device__ __forceinline__ void bar_arrive2(uint32_t sel) {
  asm volatile("{\n.reg .pred p;\nsetp.eq.u32 p, %0, 0;\n@p bar.arrive %1, %3;\n@!p bar.arrive %2, %3;\n}" ::"r"(sel), "n"(A), "n"(B), "n"(N) : "memory");
}
__device__ __forceinline__ void mbar_init(uint32_t bar, uint32_t count) {
  asm volatile("mbarrier.init.shared::cta.b64 [%0], %1;" ::"r"(bar), "r"(count) : "memory");
}
__device__ __forceinline__ void mbar_arrive(uint32_t bar) {
  asm volatile("mbarrier.arrive.shared::cta.b64 _, [%0];" ::"r"(bar) : "memory");
}
__device__ __forceinline__ void mbar_arrive_p(uint32_t bar, bool on) {
  asm volatile("{\n.reg .pred p;\nsetp.ne.u32 p, %1, 0;\n@p mbarrier.arrive.shared::cta.b64 _, [%0];\n}" ::"r"(bar), "r"((uint32_t)on) : "memory");
}
__device__ __forceinline__ uint32_t mbar_test(uint32_t bar, uint32_t parity) {
  uint32_t ok;
  asm volatile("{\n.reg .pred p;\nmbarrier.test_wait.parity.shared::cta.b64 p, [%1], %2;\nselp.u32 %0, 1, 0, p;\n}\n"
               : "=r"(ok) : "r"(bar), "r"(parity) : "memory");
  return ok;
}
__device__ __forceinline__ void mbar_wait(uint32_t bar, uint32_t parity) {
  uint32_t ok, it = 0;
  do {
    asm volatile("{\n.reg .pred p;\nmbarrier.try_wait.parity.shared::cta.b64 p, [%1], %2, %3;\nselp.u32 %0, 1, 0, p;\n}\n"
                 : "=r"(ok) : "r"(bar), "r"(parity), "r"(20000) : "memory");
  } while (!ok && ++it < (1u << 16));
}
__device__ __forceinline__ void wgmma_fence() { asm volatile("wgmma.fence.sync.aligned;" ::: "memory"); }
__device__ __forceinline__ void wgmma_commit() { asm volatile("wgmma.commit_group.sync.aligned;" ::: "memory"); }
template <int N>
__device__ __forceinline__ void wgmma_wait() { asm volatile("wgmma.wait_group.sync.aligned %0;" ::"n"(N) : "memory"); }
__device__ __forceinline__ void fence_proxy_async() { asm volatile("fence.proxy.async.shared::cta;" ::: "memory"); }

__device__ __forceinline__ uint32_t hmul2(uint32_t a, uint32_t b) {
  uint32_t d;
  asm("mul.rn.f16x2 %0, %1, %2;" : "=r"(d) : "r"(a), "r"(b));
  return d;
}
__device__ __forceinline__ uint32_t hadd2(uint32_t a, uint32_t b) {
  uint32_t d;
  asm("add.rn.f16x2 %0, %1, %2;" : "=r"(d) : "r"(a), "r"(b));
  return d;
}
__device__ __forceinline__ uint32_t hfma2(uint32_t a, uint32_t b, uint32_t c) {
  uint32_t d;
  asm("fma.rn.f16x2 %0, %1, %2, %3;" : "=r"(d) : "r"(a), "r"(b), "r"(c));
  return d;
}
__device__ __forceinline__ uint32_t bias_relu2(uint32_t x, uint32_t nb) {
  uint32_t d;
  asm("max.NaN.f16x2 %0, %1, %2;" : "=r"(d) : "r"(x), "r"(nb));
  return d;
}
__device__ __forceinline__ uint32_t habsmax2(uint32_t a, uint32_t b) {
  uint32_t d;
  asm("max.NaN.xorsign.abs.f16x2 %0, %1, %2;" : "=r"(d) : "r"(a), "r"(b));
  return d;
}
__device__ __forceinline__ uint32_t babsmax2(uint32_t a, uint32_t b) {
  uint32_t d;
  asm("max.NaN.xorsign.abs.bf16x2 %0, %1, %2;" : "=r"(d) : "r"(a), "r"(b));
  return d;
}
__device__ __forceinline__ uint32_t bf2h(uint32_t x) {
  uint32_t d;
  asm("cvt.rn.f16x2.f32 %0, %1, %2;" : "=r"(d) : "f"(__uint_as_float(x & 0xffff0000u)), "f"(__uint_as_float(x << 16)));
  return d;
}
__device__ __forceinline__ uint32_t bf2h_x16(uint32_t x) {
  uint32_t hi, lo, d;
  asm("fma.rn.bf16x2 %0, %1, %2, %3;" : "=r"(hi) : "r"(x), "r"(0x41800000u), "r"(0u));
  asm("{\n.reg .b16 l, h;\n.reg .b32 t;\nmov.b32 {l, h}, %1;\nmov.b32 t, {l, l};\nfma.rn.bf16x2 %0, t, %2, %3;\n}"
      : "=r"(lo) : "r"(x), "r"(0x41800000u), "r"(0u));
  asm("cvt.rn.f16x2.f32 %0, %1, %2;" : "=r"(d) : "f"(__uint_as_float(hi)), "f"(__uint_as_float(lo)));
  return d;
}
template <bool HI_FMA>
__device__ __forceinline__ uint32_t bf2h_f(uint32_t x) {
  uint32_t hi = x & 0xffff0000u, lo, d;
  if (HI_FMA) asm("fma.rn.bf16x2 %0, %1, %2, %3;" : "=r"(hi) : "r"(x), "r"(0x3f800000u), "r"(0u));
  asm("{\n.reg .b16 l, h;\n.reg .b32 t;\nmov.b32 {l, h}, %1;\nmov.b32 t, {l, l};\nfma.rn.bf16x2 %0, t, %2, %3;\n}"
      : "=r"(lo) : "r"(x), "r"(0x3f800000u), "r"(0u));
  asm("cvt.rn.f16x2.f32 %0, %1, %2;" : "=r"(d) : "f"(__uint_as_float(hi)), "f"(__uint_as_float(lo)));
  return d;
}
__device__ __forceinline__ uint4 convert(uint4 v) { return make_uint4(bf2h(v.x), bf2h(v.y), bf2h(v.z), bf2h(v.w)); }
__device__ __forceinline__ uint4 convert_f(uint4 v) {
  return make_uint4(bf2h_f<false>(v.x), bf2h_f<true>(v.y), bf2h_f<false>(v.z), bf2h_f<true>(v.w));
}
__device__ __forceinline__ float h_lo(uint32_t x) { return __half2float(__ushort_as_half((unsigned short)(x & 0xffffu))); }
__device__ __forceinline__ float h_hi(uint32_t x) { return __half2float(__ushort_as_half((unsigned short)(x >> 16))); }
__device__ __forceinline__ uint32_t redux_max(uint32_t v) {
  uint32_t d;
  asm volatile("redux.sync.max.u32 %0, %1, 0xffffffff;" : "=r"(d) : "r"(v));
  return d;
}
__device__ __forceinline__ uint32_t absmax_bits(uint32_t m) { return max(m & 0x7fffu, (m >> 16) & 0x7fffu); }

template <int OFF>
__device__ __forceinline__ uint4 lds128(uint32_t addr) {
  uint4 v;
  asm volatile("ld.shared.v4.u32 {%0,%1,%2,%3}, [%4+%5];" : "=r"(v.x), "=r"(v.y), "=r"(v.z), "=r"(v.w) : "r"(addr), "n"(OFF));
  return v;
}
template <int OFF>
__device__ __forceinline__ void sts128(uint32_t addr, uint4 v) {
  asm volatile("st.shared.v4.u32 [%0+%5], {%1,%2,%3,%4};" ::"r"(addr), "r"(v.x), "r"(v.y), "r"(v.z), "r"(v.w), "n"(OFF) : "memory");
}
__device__ __forceinline__ uint32_t lds32(uint32_t addr) {
  uint32_t v;
  asm volatile("ld.shared.u32 %0, [%1];" : "=r"(v) : "r"(addr));
  return v;
}
__device__ __forceinline__ void sts32(uint32_t addr, uint32_t v) { asm volatile("st.shared.u32 [%0], %1;" ::"r"(addr), "r"(v) : "memory"); }
__device__ __forceinline__ uint32_t ldg32(const void* p) {
  uint32_t v;
  asm volatile("ld.global.u32 %0, [%1];" : "=r"(v) : "l"(p) : "memory");
  return v;
}
__device__ __forceinline__ uint4 ldg128(const void* p) {
  uint4 v;
  asm volatile("ld.global.v4.u32 {%0,%1,%2,%3}, [%4];" : "=r"(v.x), "=r"(v.y), "=r"(v.z), "=r"(v.w) : "l"(p) : "memory");
  return v;
}
__device__ __forceinline__ uint2 ldg64(const void* p) {
  uint2 v;
  asm volatile("ld.global.v2.u32 {%0,%1}, [%2];" : "=r"(v.x), "=r"(v.y) : "l"(p) : "memory");
  return v;
}
__device__ __forceinline__ uint2 ldg64p(const void* p, bool on) {
  uint2 v;
  asm volatile("{\n.reg .pred p;\nsetp.ne.u32 p, %3, 0;\n@p ld.volatile.global.v2.u32 {%0,%1}, [%2];\n}" : "=r"(v.x), "=r"(v.y) : "l"(p), "r"((uint32_t)on) : "memory");
  return v;
}
__device__ __forceinline__ void ldg_idx4(uint2& x, uint2& y, const void* base, uint32_t off, bool on0, bool on1) {
  asm volatile("{\n.reg .pred p, q;\n.reg .b64 a;\n.reg .b32 lo, hi;\nsetp.ne.u32 p, %6, 0;\nsetp.ne.u32 q, %7, 0;\n"
               "mov.b64 {lo, hi}, %4;\nadd.cc.u32 lo, lo, %5;\naddc.u32 hi, hi, 0;\nmov.b64 a, {lo, hi};\n"
               "@p ld.volatile.global.v2.u32 {%0,%1}, [a];\n@q ld.volatile.global.v2.u32 {%2,%3}, [a+8];\n}"
               : "=r"(x.x), "=r"(x.y), "=r"(y.x), "=r"(y.y) : "l"(base), "r"(off), "r"((uint32_t)on0), "r"((uint32_t)on1) : "memory");
}
__device__ __forceinline__ uint4 ldg_row(const void* base, uint32_t row, bool on) {
  uint4 v;
  asm volatile("{\n.reg .pred p;\n.reg .b64 a;\nsetp.ne.u32 p, %6, 0;\nmad.wide.u32 a, %5, 256, %4;\n@p ld.global.v4.u32 {%0,%1,%2,%3}, [a];\n}"
               : "=r"(v.x), "=r"(v.y), "=r"(v.z), "=r"(v.w) : "l"(base), "r"(row), "r"((uint32_t)on) : "memory");
  return v;
}
template <int OFF>
__device__ __forceinline__ void sts128p(uint32_t addr, uint4 v, bool on) {
  asm volatile("{\n.reg .pred p;\nsetp.ne.u32 p, %6, 0;\n@p st.shared.v4.u32 [%0+%5], {%1,%2,%3,%4};\n}"
               ::"r"(addr), "r"(v.x), "r"(v.y), "r"(v.z), "r"(v.w), "n"(OFF), "r"((uint32_t)on) : "memory");
}
__device__ __forceinline__ void sts32p(uint32_t addr, uint32_t v, bool on) {
  asm volatile("{\n.reg .pred p;\nsetp.ne.u32 p, %2, 0;\n@p st.shared.u32 [%0], %1;\n}" ::"r"(addr), "r"(v), "r"((uint32_t)on) : "memory");
}
__device__ __forceinline__ uint32_t shfl_xor_v(uint32_t v, int m) {
  uint32_t d;
  asm volatile("shfl.sync.bfly.b32 %0, %1, %2, 0x1f, 0xffffffff;" : "=r"(d) : "r"(v), "r"(m));
  return d;
}
template <int M>
__device__ __forceinline__ uint32_t shfl_xor(uint32_t v) {
  uint32_t d;
  asm volatile("shfl.sync.bfly.b32 %0, %1, %2, 0x1f, 0xffffffff;" : "=r"(d) : "r"(v), "n"(M));
  return d;
}
template <int I, int N, typename F>
__device__ __forceinline__ void static_for(F&& f) {
  if constexpr (I < N) {
    f(std::integral_constant<int, I>{});
    static_for<I + 1, N>(f);
  }
}
template <int N>
__device__ __forceinline__ void fence_regs(uint32_t (&r)[N]) {
#pragma unroll
  for (int i = 0; i < N; i++) asm volatile("" : "+r"(r[i])::"memory");
}
__device__ __forceinline__ void load_vec(uint32_t (&v)[16], uint32_t a) {
  const uint4 v0 = lds128<0>(a), v1 = lds128<64>(a), v2 = lds128<128>(a), v3 = lds128<192>(a);
  v[0] = v0.x; v[1] = v0.y; v[2] = v0.z; v[3] = v0.w; v[4] = v1.x; v[5] = v1.y; v[6] = v1.z; v[7] = v1.w;
  v[8] = v2.x; v[9] = v2.y; v[10] = v2.z; v[11] = v2.w; v[12] = v3.x; v[13] = v3.y; v[14] = v3.z; v[15] = v3.w;
}

template <int OFF>
__device__ __forceinline__ void sts32o(uint32_t addr, uint32_t v) {
  asm volatile("st.shared.u32 [%0+%2], %1;" ::"r"(addr), "r"(v), "n"(OFF) : "memory");
}
__device__ __forceinline__ void keep2(uint32_t& ck, uint32_t a, uint32_t b, uint32_t never) {
  asm volatile("{\n.reg .pred p;\nsetp.ne.u32 p, %3, 0;\n@p xor.b32 %0, %1, %2;\n}" : "+r"(ck) : "r"(a), "r"(b), "r"(never));
}
__device__ __forceinline__ float exp_e(uint32_t es) {
  float w;
  asm("ex2.approx.ftz.f32 %0, %1;" : "=f"(w) : "f"(h_lo(es) * (1.4426950408889634f / 256.f)));
  return w;
}
__device__ __forceinline__ uint32_t clock32() {
  uint32_t v;
  asm volatile("mov.u32 %0, %%clock;" : "=r"(v)::"memory");
  return v;
}
__device__ __forceinline__ void sched_fence(uint32_t& ck, uint32_t never) {
  asm volatile("{\n.reg .pred p;\nsetp.ne.u32 p, %1, 0;\n@p mov.u32 %0, %%clock;\n}" : "+r"(ck) : "r"(never) : "memory");
}

template <int ACCUM>
__device__ __forceinline__ void wgmma_rs_n128(uint32_t (&d)[32], uint32_t a0, uint32_t a1, uint32_t a2, uint32_t a3, uint64_t descB) {
  if (ACCUM == 1) {
    asm volatile(
        "wgmma.mma_async.sync.aligned.m64n128k16.f16.f16.f16 "
        "{%0, %1, %2, %3, %4, %5, %6, %7, %8, %9, %10, %11, %12, %13, %14, %15, %16, %17, %18, %19, %20, %21, %22, %23, %24, %25, %26, %27, %28, %29, %30, %31}, "
        "{%32, %33, %34, %35}, %36, 1, 1, 1, 1;\n"
        : "+r"(d[0]), "+r"(d[1]), "+r"(d[2]), "+r"(d[3]), "+r"(d[4]), "+r"(d[5]), "+r"(d[6]), "+r"(d[7]), "+r"(d[8]), "+r"(d[9]), "+r"(d[10]), "+r"(d[11]), "+r"(d[12]), "+r"(d[13]), "+r"(d[14]), "+r"(d[15]), "+r"(d[16]), "+r"(d[17]), "+r"(d[18]), "+r"(d[19]), "+r"(d[20]), "+r"(d[21]), "+r"(d[22]), "+r"(d[23]), "+r"(d[24]), "+r"(d[25]), "+r"(d[26]), "+r"(d[27]), "+r"(d[28]), "+r"(d[29]), "+r"(d[30]), "+r"(d[31])
        : "r"(a0), "r"(a1), "r"(a2), "r"(a3), "l"(descB));
  }
  if (ACCUM == 0) {
    asm volatile(
        "wgmma.mma_async.sync.aligned.m64n128k16.f16.f16.f16 "
        "{%0, %1, %2, %3, %4, %5, %6, %7, %8, %9, %10, %11, %12, %13, %14, %15, %16, %17, %18, %19, %20, %21, %22, %23, %24, %25, %26, %27, %28, %29, %30, %31}, "
        "{%32, %33, %34, %35}, %36, 0, 1, 1, 1;\n"
        : "=r"(d[0]), "=r"(d[1]), "=r"(d[2]), "=r"(d[3]), "=r"(d[4]), "=r"(d[5]), "=r"(d[6]), "=r"(d[7]), "=r"(d[8]), "=r"(d[9]), "=r"(d[10]), "=r"(d[11]), "=r"(d[12]), "=r"(d[13]), "=r"(d[14]), "=r"(d[15]), "=r"(d[16]), "=r"(d[17]), "=r"(d[18]), "=r"(d[19]), "=r"(d[20]), "=r"(d[21]), "=r"(d[22]), "=r"(d[23]), "=r"(d[24]), "=r"(d[25]), "=r"(d[26]), "=r"(d[27]), "=r"(d[28]), "=r"(d[29]), "=r"(d[30]), "=r"(d[31])
        : "r"(a0), "r"(a1), "r"(a2), "r"(a3), "l"(descB));
  }
}
template <int ACCUM>
__device__ __forceinline__ void wgmma_rs_n96(uint32_t (&d)[24], uint32_t a0, uint32_t a1, uint32_t a2, uint32_t a3, uint64_t descB) {
  if (ACCUM == 1) {
    asm volatile(
        "wgmma.mma_async.sync.aligned.m64n96k16.f16.f16.f16 "
        "{%0, %1, %2, %3, %4, %5, %6, %7, %8, %9, %10, %11, %12, %13, %14, %15, %16, %17, %18, %19, %20, %21, %22, %23}, "
        "{%24, %25, %26, %27}, %28, 1, 1, 1, 1;\n"
        : "+r"(d[0]), "+r"(d[1]), "+r"(d[2]), "+r"(d[3]), "+r"(d[4]), "+r"(d[5]), "+r"(d[6]), "+r"(d[7]), "+r"(d[8]), "+r"(d[9]), "+r"(d[10]), "+r"(d[11]), "+r"(d[12]), "+r"(d[13]), "+r"(d[14]), "+r"(d[15]), "+r"(d[16]), "+r"(d[17]), "+r"(d[18]), "+r"(d[19]), "+r"(d[20]), "+r"(d[21]), "+r"(d[22]), "+r"(d[23])
        : "r"(a0), "r"(a1), "r"(a2), "r"(a3), "l"(descB));
  }
  if (ACCUM == 0) {
    asm volatile(
        "wgmma.mma_async.sync.aligned.m64n96k16.f16.f16.f16 "
        "{%0, %1, %2, %3, %4, %5, %6, %7, %8, %9, %10, %11, %12, %13, %14, %15, %16, %17, %18, %19, %20, %21, %22, %23}, "
        "{%24, %25, %26, %27}, %28, 0, 1, 1, 1;\n"
        : "=r"(d[0]), "=r"(d[1]), "=r"(d[2]), "=r"(d[3]), "=r"(d[4]), "=r"(d[5]), "=r"(d[6]), "=r"(d[7]), "=r"(d[8]), "=r"(d[9]), "=r"(d[10]), "=r"(d[11]), "=r"(d[12]), "=r"(d[13]), "=r"(d[14]), "=r"(d[15]), "=r"(d[16]), "=r"(d[17]), "=r"(d[18]), "=r"(d[19]), "=r"(d[20]), "=r"(d[21]), "=r"(d[22]), "=r"(d[23])
        : "r"(a0), "r"(a1), "r"(a2), "r"(a3), "l"(descB));
  }
}
template <int ACCUM>
__device__ __forceinline__ void wgmma_rs_n32(uint32_t (&d)[8], uint32_t a0, uint32_t a1, uint32_t a2, uint32_t a3, uint64_t descB) {
  if (ACCUM == 1) {
    asm volatile(
        "wgmma.mma_async.sync.aligned.m64n32k16.f16.f16.f16 "
        "{%0, %1, %2, %3, %4, %5, %6, %7}, "
        "{%8, %9, %10, %11}, %12, 1, 1, 1, 1;\n"
        : "+r"(d[0]), "+r"(d[1]), "+r"(d[2]), "+r"(d[3]), "+r"(d[4]), "+r"(d[5]), "+r"(d[6]), "+r"(d[7])
        : "r"(a0), "r"(a1), "r"(a2), "r"(a3), "l"(descB));
  }
  if (ACCUM == 0) {
    asm volatile(
        "wgmma.mma_async.sync.aligned.m64n32k16.f16.f16.f16 "
        "{%0, %1, %2, %3, %4, %5, %6, %7}, "
        "{%8, %9, %10, %11}, %12, 0, 1, 1, 1;\n"
        : "=r"(d[0]), "=r"(d[1]), "=r"(d[2]), "=r"(d[3]), "=r"(d[4]), "=r"(d[5]), "=r"(d[6]), "=r"(d[7])
        : "r"(a0), "r"(a1), "r"(a2), "r"(a3), "l"(descB));
  }
}

__device__ __forceinline__ float rbf(float x) { return __bfloat162float(__float2bfloat16_rn(x)); }
__device__ __forceinline__ float warp_sum(float v) {
#pragma unroll
  for (int o = 16; o > 0; o >>= 1) v += __shfl_xor_sync(0xffffffffu, v, o);
  return v;
}

__device__ __noinline__ void general_element(const int* __restrict__ idx, const __nv_bfloat16* __restrict__ table,
                                             const int* __restrict__ ii, const int* __restrict__ jj,
                                             const __nv_bfloat16* __restrict__ W, const __nv_bfloat16* __restrict__ bias,
                                             const __nv_bfloat16* __restrict__ hvec, const __nv_bfloat16* __restrict__ pvec,
                                             __nv_bfloat16* __restrict__ out, float* ev) {
  const int lane = threadIdx.x & 31;
  auto pair4 = [&](int p, float (&pr)[4]) {
    const __nv_bfloat16* a = table + (size_t)idx[ii[p]] * kD + 4 * lane;
    const __nv_bfloat16* b = table + (size_t)idx[jj[p]] * kD + 4 * lane;
#pragma unroll
    for (int q = 0; q < 4; q++) pr[q] = rbf(__bfloat162float(a[q]) * __bfloat162float(b[q]));
  };
  float m = -INFINITY;
  bool has_nan = false;
  for (int p = 0; p < kP; p++) {
    float pr[4], x[4] = {0.f, 0.f, 0.f, 0.f};
    pair4(p, pr);
    for (int l = 0; l < 32; l++) {
#pragma unroll
      for (int q = 0; q < 4; q++) {
        const float v = __shfl_sync(0xffffffffu, pr[q], l);
        const uint2 w = *reinterpret_cast<const uint2*>(W + (4 * l + q) * kD + 4 * lane);
        x[0] = fmaf(v, __uint_as_float(w.x << 16), x[0]);
        x[1] = fmaf(v, __uint_as_float(w.x & 0xffff0000u), x[1]);
        x[2] = fmaf(v, __uint_as_float(w.y << 16), x[2]);
        x[3] = fmaf(v, __uint_as_float(w.y & 0xffff0000u), x[3]);
      }
    }
    float e = 0.f;
#pragma unroll
    for (int q = 0; q < 4; q++) {
      const float y = rbf(rbf(x[q]) + __bfloat162float(bias[4 * lane + q]));
      e = fmaf(rbf(0.5f * rbf(y + fabsf(y))), __bfloat162float(hvec[4 * lane + q]), e);
    }
    e = rbf(warp_sum(e));
    has_nan |= (e != e);
    m = fmaxf(m, e);
    if (lane == 0) ev[p] = e;
  }
  __syncwarp();
  float l = 0.f;
  for (int p = lane; p < kP; p += 32) l += expf(ev[p] - m);
  l = warp_sum(l);
  float pooled[4] = {0.f, 0.f, 0.f, 0.f};
  for (int p = 0; p < kP; p++) {
    float pr[4];
    pair4(p, pr);
    const float al = rbf(expf(ev[p] - m) / l);
#pragma unroll
    for (int q = 0; q < 4; q++) pooled[q] = fmaf(al, pr[q], pooled[q]);
  }
  float o = 0.f;
#pragma unroll
  for (int q = 0; q < 4; q++) o = fmaf(rbf(pooled[q]), __bfloat162float(pvec[4 * lane + q]), o);
  o = warp_sum(o);
  if (has_nan) o = __int_as_float(0x7fffffff);
  if (lane == 0) *out = __float2bfloat16_rn(o);
}

__device__ __forceinline__ void helper_rest(const int* __restrict__ idx, const __nv_bfloat16* __restrict__ table,
                                            const __nv_bfloat16* __restrict__ W, const Late& late, int per, int n_elem,
                                            int n_left, uint8_t* smem) {
  constexpr uint32_t sbase = 0x400u;
  uint32_t tid, cta;
  asm volatile("mov.u32 %0, %%tid.x;\nmov.u32 %1, %%ctaid.x;" : "=r"(tid), "=r"(cta));
  const int t = tid & 127, lane = tid & 31, wq = (tid >> 5) & 3;
  cta -= n_left;
  const int b0 = cta * per, last_row = n_elem * kF - 2;
  const int n_out = min(per, n_elem - b0), n_c = max(n_out, 2);
  const int grp = 7 - (t >> 4);
  const bool v01 = grp < 7, v23 = grp < 6;
  int irow = (b0 + (n_c > 2 ? 2 : 0)) * kF + 4 * grp;
  uint2 gi01 = ldg64(idx + min(irow, last_row));
  uint2 gi23 = ldg64(idx + min(irow + 2, last_row));
  const __nv_bfloat16* gsrc = table + (t & 15) * 8;
  uint32_t cv_ptr = sbase + OFF_EMB + 2 * kElem + 4 * grp * kRow + (t & 15) * 16;
  uint32_t me = 0, ck = 0;
  auto track = [&](const uint4& a, const uint4& b, bool on) {
    const uint32_t m = babsmax2(babsmax2(babsmax2(a.x, a.y), babsmax2(a.z, a.w)), babsmax2(babsmax2(b.x, b.y), babsmax2(b.z, b.w)));
    me = babsmax2(me, on ? m : 0u);
  };
  named_bar_sync(6, 160);
#pragma unroll 1
  for (int e = 2; e < n_c + 2; e++) {
    const uint4 g0 = ldg_row(gsrc, gi01.x, v01), g1 = ldg_row(gsrc, gi01.y, v01);
    const uint4 g2 = ldg_row(gsrc, gi23.x, v23), g3 = ldg_row(gsrc, gi23.y, v23);
    irow += e + 1 == n_c ? (1 - n_c) * kF : kF;
    gi01 = ldg64(idx + min(irow, last_row));
    gi23 = ldg64(idx + min(irow + 2, last_row));
    uint4 h0 = convert(g0), h1 = convert(g1), h2 = convert(g2), h3 = convert(g3);
    asm volatile("" : "+r"(h0.x), "+r"(h0.y), "+r"(h0.z), "+r"(h0.w), "+r"(h1.x), "+r"(h1.y), "+r"(h1.z), "+r"(h1.w),
                      "+r"(h2.x), "+r"(h2.y), "+r"(h2.z), "+r"(h2.w), "+r"(h3.x), "+r"(h3.y), "+r"(h3.z), "+r"(h3.w));
    sched_fence(ck, tid >> 10);
    sts128p<0>(cv_ptr, h0, v01 && e < n_c);
    sts128p<kRow>(cv_ptr, h1, v01 && e < n_c);
    sts128p<2 * kRow>(cv_ptr, h2, v23 && e < n_c);
    sts128p<3 * kRow>(cv_ptr, h3, v23 && e < n_c);
    __syncwarp();
    mbar_arrive_p(sbase + OFF_BAR + 8 * e, lane == 0 && e < n_c);
    sched_fence(ck, tid >> 10);
    cv_ptr += kElem;
    track(g0, g1, v01);
    track(g2, g3, v23);
  }
  bool ok_cta;
  float ds;
  {
    const uint32_t s0 = ldg32(late.vec[t >> 6] + 2 * (t & 63)), s1 = ldg32(late.vec[2] + 2 * (t & 63));
    const uint32_t s2 = ldg32(late.vec[(t >> 6) ^ 1] + 2 * (t & 63));
    uint32_t pi[3], pj[3];
#pragma unroll
    for (int r = 0; r < 3; r++) {
      pi[r] = ldg32(late.ii + min(t + 128 * r, kP - 1));
      pj[r] = ldg32(late.jj + min(t + 128 * r, kP - 1));
    }
    float v0 = 16.f * (fabsf(__uint_as_float(s0 << 16)) + fabsf(__uint_as_float(s0 & 0xffff0000u)));
    float v1 = 16.f * (fabsf(__uint_as_float(s1 << 16)) + fabsf(__uint_as_float(s1 & 0xffff0000u)));
    if (t >= 64) v1 = fabsf(__uint_as_float(s0 << 16) * __uint_as_float(s2 << 16)) +
                      fabsf(__uint_as_float(s0 & 0xffff0000u) * __uint_as_float(s2 & 0xffff0000u));
    bool good = true;
#pragma unroll
    for (int r = 0; r < 3; r++)
      good &= (pi[r] < pj[r]) & (pj[r] < kF) & (((pi[r] * (2 * kF - 1 - pi[r])) >> 1) + pj[r] - pi[r] - 1 == min(t + 128 * r, kP - 1));
    if (!good) v0 = __int_as_float(0x7fffffff);
    v0 = warp_sum(v0);
    v1 = warp_sum(v1);
    sts32p(sbase + OFF_STAT + 64 + wq * 4, __float_as_uint(v0), lane == 0);
    sts32p(sbase + OFF_STAT + 80 + wq * 4, __float_as_uint(v1), lane == 0);
    sts32p(sbase + OFF_STAT + 16 + wq * 4 + ck, redux_max(absmax_bits(me)), lane == 0);
    named_bar_sync(6, 128);
    const uint32_t st = lds32(sbase + OFF_STAT + lane * 4);
    const float Wm = 2048.f * __uint_as_float(redux_max(lane < 4 ? st : 0u) << 16);
    const float M = __uint_as_float(redux_max(lane >= 4 && lane < 8 ? st : 0u) << 16);
    const float sp = __uint_as_float(st) + __shfl_xor_sync(0xffffffffu, __uint_as_float(st), 1);
    const float Bs = __shfl_sync(0xffffffffu, sp, 16);
    const float Hs = __shfl_sync(0xffffffffu, sp, 18);
    const float Ps = __shfl_sync(0xffffffffu, sp, 20);
    const float HB = __shfl_sync(0xffffffffu, sp, 22);
    const float M2 = M * M, X = fmaf(M2, Wm, Bs), G = fmaf(2.f, M, 1.f);
    constexpr float u = 1.f / 33554432.f;
    const float de = u * (Hs * (Wm * G + 128.f * M2 + 16.f) + 128.f * X + 256.f);
    ds = u * (Ps * G + 128.f * M2 + 256.f);
    ok_cta = M2 <= 60000.f && Wm <= 128.f * 60000.f && X <= 60000.f && Hs <= 60000.f && Ps <= 60000.f && de <= 1.f && HB <= 64.f;
  }
#pragma unroll 1
  for (int e = wq; e < n_c; e += 4) {
    const uint32_t ea = sbase + OFF_ES + (2 + e) * ES_STRIDE + lane * 16;
    float l = 0.f, a = 0.f;
    if (lane == 0 && e < n_out) {
      float2* const gp = g_left + b0 + e;
      for (uint32_t it = 0; it < (1u << 22); it++) {
        asm volatile("{\n.reg .b64 v;\nld.volatile.global.b64 v, [%2];\nmov.b64 {%0,%1}, v;\n}" : "=f"(l), "=f"(a) : "l"(gp) : "memory");
        if (__float_as_uint(l) != 0u) break;
        __nanosleep(200);
      }
      asm volatile("st.volatile.global.b64 [%0], %1;" ::"l"(gp), "l"(0ull) : "memory");
    }
    __syncwarp();
    uint32_t mx = lane == 0 && !(l > 0.f) ? 0x7fffu : 0u;
    auto take = [&](const uint4& v) {
      const uint32_t es = hadd2(hadd2(v.x, v.y), hadd2(v.z, v.w));
      const float w = exp_e(es);
      mx = habsmax2(mx, es);
      l = fmaf(w, 16.f, l);
      a = fmaf(w, h_hi(es), a);
    };
    l *= 16.f;
    const bool last = e + 2 >= n_c;
    if (last) named_bar_sync(13 + (e & 1), 160);
    else mbar_wait(sbase + OFF_BAR + 80 + 8 * e, 0);
    {
      uint4 v[6];
      static_for<0, 6>([&](auto Qc) { v[decltype(Qc)::value] = lds128<decltype(Qc)::value * 512>(ea); });
      sched_fence(ck, tid >> 10);
#pragma unroll
      for (int q = 0; q < 6; q++) take(v[q]);
    }
    __nv_bfloat16* op = late.out + b0 + e;
    uint32_t wr = lane == 0 && e < n_out;
    asm volatile("" : "+l"(op), "+r"(wr));
    if (last) named_bar_sync(10 + (e & 1), 160);
    take(lds128<3072>(ea));
    take(lds128<3072 + 512>(ea));
    asm volatile("" : "+f"(l), "+f"(a), "+r"(mx));
    sched_fence(ck, tid >> 10);
    asm volatile("{\n.reg .pred p, q;\nsetp.ne.u32 q, %1, 0;\nsetp.eq.and.u32 p|q, %0, 0, q;\n@p bar.sync 8, 160;\n@q bar.sync 9, 160;\n}"
                 ::"r"(e & 1), "r"((uint32_t)last) : "memory");
    {
      const uint4 v0 = lds128<4096>(ea + ck), v1 = lds128<4096 + 512>(ea);
      take(v0);
      take(v1);
    }
    const uint32_t big = __ballot_sync(0xffffffffu, ds <= fabsf(h_hi(mx)) * (1.f / 16384.f));
    const uint32_t bad = __ballot_sync(0xffffffffu, ((mx & 0x7fffu) > 0x7000u) | ((mx & 0x7c000000u) == 0x7c000000u));
    const bool ok = (big != 0u) & (bad == 0u) & ok_cta;
#pragma unroll
    for (int o = 0; o < 5; o++) {
      l += __uint_as_float(shfl_xor_v(__float_as_uint(l), 1 << o));
      a += __uint_as_float(shfl_xor_v(__float_as_uint(a), 1 << o));
    }
    float r;
    asm("rcp.approx.ftz.f32 %0, %1;" : "=f"(r) : "f"(l));
    asm volatile("{\n.reg .pred p;\n.reg .b16 h;\nsetp.ne.u32 p, %2, 0;\ncvt.rn.bf16.f32 h, %1;\n@p st.global.b16 [%0], h;\n}"
                 ::"l"(op), "f"(a * r), "r"(wr) : "memory");
    if (!ok && e < n_out)
      general_element(idx + (b0 + e) * kF, table, late.ii, late.jj, W, late.vec[0], late.vec[1], late.vec[2], op, reinterpret_cast<float*>(smem + OFF_EMB + e * kElem));
  }
}

__global__ void __launch_bounds__(kThreads, 1)
afm_kernel(const int* __restrict__ idx, const __nv_bfloat16* __restrict__ table, const __nv_bfloat16* __restrict__ W,
           uint32_t ix_stride, uint32_t ix_bias, uint32_t ix_last, int per, int n_elem, int n_left,
           const __grid_constant__ Late late) {
  extern __shared__ __align__(1024) uint8_t smem[];
  constexpr uint32_t sbase = 0x400u;

  const int tid = threadIdx.x;
  const int t = tid & 127;
  const int lane = tid & 31;
  const int warp = tid >> 5;
  uint32_t ck = 0;
  uint32_t never = tid >> 10;
  const int grp = 7 - (t >> 4);
  const bool v01 = grp < 7, v23 = grp < 6;
  const bool is_left = (int)blockIdx.x < n_left;
  const uint32_t ioff = blockIdx.x * ix_stride - ix_bias + ((tid >> 7) * kF + 4 * grp) * 4;
  uint2 gi01, gi23;
  ldg_idx4(gi01, gi23, idx, ioff <= ix_last ? ioff : 0u, v01 && tid < 256, v23 && tid < 256);
  asm volatile("{\n.reg .pred p;\nsetp.ge.u32 p, %1, %2;\n@p prefetch.global.L2 [%0];\n}" ::"l"(W + ((blockIdx.x * 32 + tid) & 255) * 64), "r"(tid), "n"(384 - 32) : "memory");
  sched_fence(ck, never);
  const int wq = warp & 3;
  const int wg = __shfl_sync(0xffffffffu, tid >> 7, 0);
  const int n_c = max(min(per, n_elem - ((int)blockIdx.x - n_left) * per), 2);
  const __nv_bfloat16* gsrc = table + (t & 15) * 8;
  asm volatile("" : "+l"(gsrc));
  uint32_t cv_ptr = sbase + OFF_EMB + wg * kElem + 4 * grp * kRow + (t & 15) * 16;

  if (wg < 2) {
    const int c = lane & 3;
    const int tau = t >> 2;
    if (wg == 0) {
      asm volatile("cp.async.ca.shared.global [%0], [%1], 4;\ncp.async.ca.shared.global [%0+4], [%2], 4;\ncp.async.commit_group;"
                   ::"r"(sbase + OFF_ES + t * 8), "l"(late.vec[t >> 6] + 2 * (t & 63)), "l"(late.vec[2] + 2 * (t & 63)) : "memory");
    }
    const int nb = (n_c - wg + 1) >> 1;
    const uint32_t sc = late.sched.e[tau];
    uint4 g0[4];
    const bool q01 = v01 && !is_left, q23 = v23 && !is_left;
    sched_fence(ck, never);
    if (wg == 1) {
      uint32_t y;
      asm volatile("or.b32 %0, %1, %2;" : "=r"(y) : "r"(gi01.x), "r"(gi23.x));
      const uint32_t t0 = clock32() + (y >> 31);
      while (clock32() - t0 < 450) {
      }
    }
    sched_fence(ck, never);
    g0[0] = ldg_row(gsrc, gi01.x, q01);
    g0[1] = ldg_row(gsrc, gi01.y, q01);
    g0[2] = ldg_row(gsrc, gi23.x, q23);
    g0[3] = ldg_row(gsrc, gi23.y, q23);
    sched_fence(ck, never);
    const int* lip = idx + min((int)(blockIdx.x * 256 + tau * 8 + wg), n_elem - 1) * kF;
    const uint2 li01 = ldg64p(lip, is_left), li23 = ldg64p(lip + 2, is_left);
    if (warp == 0) {
      if (lane == 0) {
#pragma unroll
        for (int i = 0; i < 16; i++) mbar_init(sbase + OFF_BAR + 8 * i, i < 2 ? 1 : i < 8 ? 4 : 128);
        mbar_arrive(sbase + OFF_BAR);
        mbar_arrive(sbase + OFF_BAR + 8);
      }
      if (smem_u32(smem) != sbase) __trap();
      __syncwarp();
      named_bar_arrive(6, 160);
    }
    if (wg == 0) {
      asm volatile("cp.async.wait_group 0;" ::: "memory");
      const uint32_t s0 = lds32(sbase + OFF_ES + t * 8), s1 = lds32(sbase + OFF_ES + t * 8 + 4);
      sts32(sbase + OFF_VEC + ((t & 112u) | ((t & 3u) << 2) | ((t >> 2) & 3u)) * 4,
            bf2h_x16(s0) ^ (t < 64 ? 0x80008000u : 0u));
      sts32(sbase + OFF_VEC + 512 + (t & 63) * 4, bf2h_x16(s1));
      named_bar_arrive(12, 256);
    }
    asm volatile("{\n.reg .pred p;\nsetp.eq.u32 p, %0, 0;\n@p bar.sync 1, 128;\n@!p bar.sync 12, 256;\n}" ::"r"(wg) : "memory");
    sched_fence(ck, never);
    uint32_t bs[16], hs[16], ps[16];
    load_vec(ps, sbase + OFF_VEC + 512 + c * 16);
    load_vec(bs, sbase + OFF_VEC + c * 16);
    load_vec(hs, sbase + OFF_VEC + 256 + c * 16);
    sched_fence(ck, never);
    if (wg == 1) named_bar_sync(7, 256);
    asm volatile("setmaxnreg.inc.sync.aligned.u32 %0;" ::"n"(216));
    if (wg == 0) named_bar_arrive(7, 256);
    uint32_t pt_ptr = shfl_xor<0>(sbase + OFF_ES + (2 + wg) * ES_STRIDE + t * 4);
    never = pt_ptr >> 31;
    uint32_t ra[6];
#pragma unroll
    for (int r = 0; r < 6; r++) ra[r] = sbase + OFF_EMB + wg * kElem + c * 16 + ((sc >> (5 * r)) & 31u) * kRow;
    asm volatile("" : "+r"(ra[0]), "+r"(ra[1]), "+r"(ra[2]), "+r"(ra[3]), "+r"(ra[4]), "+r"(ra[5]));
    sched_fence(ck, never);
    uint32_t Af[32], acc[32], S0[16], S1[16], S2[16], S3[16];
    constexpr uint64_t dB = (uint64_t)(((sbase + OFF_B) & 0x3FFFFu) >> 4) | ((uint64_t)(B_NBLK >> 4) << 16) |
                            ((uint64_t)(1024 >> 4) << 32) | ((uint64_t)1 << 62);
    auto products = [&](const uint32_t (&X)[16], const uint32_t (&Y)[16], const uint32_t (&Z)[16]) {
#pragma unroll
      for (int i = 0; i < 16; i++) {
        Af[2 * i] = hmul2(X[i], Z[i]);
        Af[2 * i + 1] = hmul2(Y[i], Z[i]);
      }
    };
    auto mma_tile = [&]() {
      fence_regs(Af);
      wgmma_fence();
#pragma unroll
      for (int s = 0; s < 8; s++) {
        const uint64_t d = dB + (uint64_t)(s * (2048 >> 4));
        if (s == 0) wgmma_rs_n128<0>(acc, Af[0], Af[1], Af[2], Af[3], d);
        else wgmma_rs_n128<1>(acc, Af[4 * s], Af[4 * s + 1], Af[4 * s + 2], Af[4 * s + 3], d);
      }
      wgmma_commit();
    };
    auto issue = [&]() {
      mma_tile();
      bar_arrive2<5, 4>(wg);
    };
    uint32_t eh0 = 0, eh1 = 0, sh0 = 0, sh1 = 0;
    auto fold = [&]() {
      eh0 = hadd2(__byte_perm(eh0, sh0, 0x5410), __byte_perm(eh0, sh0, 0x7632));
      eh1 = hadd2(__byte_perm(eh1, sh1, 0x5410), __byte_perm(eh1, sh1, 0x7632));
    };
    auto s_chain = [&]() {
      sh0 = hmul2(Af[0], ps[0]);
      sh1 = hmul2(Af[1], ps[0]);
#pragma unroll
      for (int i = 1; i < 16; i++) {
        sh0 = hfma2(Af[2 * i], ps[i], sh0);
        sh1 = hfma2(Af[2 * i + 1], ps[i], sh1);
      }
      asm volatile("" : "+r"(sh0), "+r"(sh1)::"memory");
    };
    auto epilogue = [&]() {
      wgmma_wait<0>();
      fence_regs(acc);
      fence_regs(S0); fence_regs(S1); fence_regs(S2); fence_regs(S3);
      eh0 = hmul2(bias_relu2(acc[0], bs[0]), hs[0]);
      eh1 = hmul2(bias_relu2(acc[1], bs[0]), hs[0]);
#pragma unroll
      for (int i = 1; i < 16; i++) {
        eh0 = hfma2(bias_relu2(acc[2 * i], bs[i]), hs[i], eh0);
        eh1 = hfma2(bias_relu2(acc[2 * i + 1], bs[i]), hs[i], eh1);
      }
      asm volatile("" : "+r"(eh0), "+r"(eh1)::"memory");
    };
    if (is_left) {
      if (wg == 1) named_bar_arrive(4, 256);
      const int e0 = shfl_xor<0>(blockIdx.x * 256 + tau * 8 + wg);
      const __nv_bfloat16* lsrc = table + c * 8;
      uint32_t ia, ib, ic, id, ma;
      float lsum = 0.f, asum = 0.f;
      auto load_ix = [&](int r) {
        const int* ip = idx + min(e0 + 2 * r, n_elem - 1) * kF;
        const uint2 x = ldg64(ip), y = ldg64(ip + 2);
        ia = x.x; ib = x.y; ic = y.x; id = y.y;
      };
      auto load_row = [&](uint32_t (&v)[16], uint32_t row) {
#pragma unroll
        for (int kb = 0; kb < 4; kb++) {
          const uint4 x = ldg_row(lsrc + 32 * kb, row, true);
          v[4 * kb] = x.x; v[4 * kb + 1] = x.y; v[4 * kb + 2] = x.z; v[4 * kb + 3] = x.w;
        }
      };
      auto cvt_row = [&](uint32_t (&v)[16]) {
#pragma unroll
        for (int i = 0; i < 16; i++) v[i] = bf2h(v[i]);
      };
      auto finish = [&](bool one_row) {
        s_chain();
        sched_fence(ck, never);
        epilogue();
        fold();
        uint32_t es = hadd2((c & 1) ? eh1 : eh0, shfl_xor<1>((c & 1) ? eh0 : eh1));
        es = hadd2(es, shfl_xor<2>(es));
        const float w = one_row && (c & 1) ? 0.f : exp_e(es);
        ma = habsmax2(ma, es);
        lsum += w;
        asum = fmaf(w, h_hi(es), asum);
        sched_fence(ck, never);
      };
      ia = li01.x; ib = li01.y; ic = li23.x; id = li23.y;
      load_row(S0, ia); load_row(S1, ib); load_row(S2, ic); load_row(S3, id);
      if (wg == 0) named_bar_sync(3, 256);
#pragma unroll 1
      for (int r = 0; r < 4; r++) {
        const int e = e0 + 2 * r;
        load_ix(r + 1);
        lsum = 0.f; asum = 0.f; ma = 0;
        cvt_row(S0); cvt_row(S1);
        products(S0, S0, S1);
        bar_sync2<4, 5>(wg);
        issue();
        cvt_row(S2); cvt_row(S3);
        finish(true);
        products(S0, S1, S2);
        bar_sync2<4, 5>(wg);
        issue();
        load_row(S2, ic);
        finish(false);
        products(S0, S1, S3);
        bar_sync2<4, 5>(wg);
        issue();
        load_row(S0, ia); load_row(S1, ib); load_row(S3, id);
        finish(false);
        lsum += __shfl_xor_sync(0xffffffffu, lsum, 1);
        asum += __shfl_xor_sync(0xffffffffu, asum, 1);
        ma = habsmax2(ma, shfl_xor<1>(ma));
        if ((ma & 0x7fffu) > 0x7000u || ((ma >> 16) & 0x7fffu) >= 0x7c00u) lsum = __int_as_float(0x7fffffff);
        if (c == 0 && e < n_elem)
          asm volatile("{\n.reg .b64 v;\nmov.b64 v, {%1,%2};\nst.volatile.global.b64 [%0], v;\n}" ::"l"(g_left + e + ck), "f"(lsum), "f"(asum) : "memory");
      }
      if (wg == 0) named_bar_sync(4, 256);
      return;
    }
    sts128p<0>(cv_ptr, convert_f(g0[0]), v01);
    sts128p<kRow>(cv_ptr, convert_f(g0[1]), v01);
    sts128p<2 * kRow>(cv_ptr, convert_f(g0[2]), v23);
    sts128p<3 * kRow>(cv_ptr, convert_f(g0[3]), v23);
    asm volatile("{\n.reg .pred p;\nsetp.eq.u32 p, %0, 0;\n@p bar.sync 3, 256;\n@!p bar.sync 2, 128;\n}" ::"r"(wg) : "memory");

    static_for<0, 4>([&](auto Kc) {
      constexpr int kb = decltype(Kc)::value;
      const uint4 z = lds128<64 * kb>(ra[5]), x = lds128<64 * kb>(ra[0]), y = lds128<64 * kb>(ra[1]);
      S3[4 * kb] = z.x; S3[4 * kb + 1] = z.y; S3[4 * kb + 2] = z.z; S3[4 * kb + 3] = z.w;
      S0[4 * kb] = x.x; S0[4 * kb + 1] = x.y; S0[4 * kb + 2] = x.z; S0[4 * kb + 3] = x.w;
      S1[4 * kb] = y.x; S1[4 * kb + 1] = y.y; S1[4 * kb + 2] = y.z; S1[4 * kb + 3] = y.w;
      if (kb & 1) sched_fence(ck, never);
    });
#pragma unroll
    for (int i = 0; i < 16; i++) S2[i] = 0;
    static_for<0, 2>([&](auto Hc) {
      constexpr int h = decltype(Hc)::value, n = 16 / 2;
#pragma unroll
      for (int i = h * n; i < h * n + n; i++) {
        Af[2 * i] = hmul2(S0[i], S3[i]);
        Af[2 * i + 1] = hmul2(S1[i], S3[i]);
        asm volatile("" : "+r"(Af[2 * i]), "+r"(Af[2 * i + 1])::"memory");
      }
      if (h == 0) {
        if (wg == 1) named_bar_sync(5, 256);
        sched_fence(ck, never);
      }
      wgmma_fence();
#pragma unroll
      for (int s = h * n / 2; s < (h * n + n) / 2; s++) {
        const uint64_t d = dB + (uint64_t)(s * (2048 >> 4));
        if (s == 0) wgmma_rs_n128<0>(acc, Af[0], Af[1], Af[2], Af[3], d);
        else wgmma_rs_n128<1>(acc, Af[4 * s], Af[4 * s + 1], Af[4 * s + 2], Af[4 * s + 3], d);
      }
      sched_fence(ck, never);
    });
    wgmma_commit();
    bar_arrive2<5, 4>(wg);
    sched_fence(ck, never);

    auto bump = [&](uint32_t& r) { asm volatile("add.u32 %0, %0, %1;" : "+r"(r) : "n"(2 * kElem)); };
    int left = nb - 1;
    ra[0] += 2 * kElem; ra[1] += 2 * kElem; ra[5] += 2 * kElem;
    uint4 r0, r1;
    uint32_t el = wg, rdy = 0;
    auto tile = [&](auto Tc) {
      constexpr int tt = decltype(Tc)::value & 7;
      constexpr bool last = decltype(Tc)::value > 7;
      sched_fence(ck, never);
      fold();
      const uint32_t f0 = eh0, f1 = eh1;
      sts32o<(tt == 0 ? 4096 - 2 * ES_STRIDE : (tt - 1) * 1024)>(pt_ptr, eh0);
      sts32o<(tt == 0 ? 4096 - 2 * ES_STRIDE : (tt - 1) * 1024) + 512>(pt_ptr, eh1);
      if (tt == 0) mbar_arrive(sbase + OFF_BAR + 64 + 8 * el);
      if (last) bar_arrive2<13, 14, 160>(wg);
      if (tt == 2) rdy = mbar_test(sbase + OFF_BAR + 8 * min(el + 2, n_c - 1), 0);
      sched_fence(ck, never);
      if (tt == 0) load_vec(S0, ra[3]);
      if (tt == 1) load_vec(S2, ra[4]);
      if (tt == 2) load_vec(S1, ra[2]);
      if (tt == 3 && !last) {
        load_vec(S0, ra[0]);
        r0 = lds128<0>(ra[1]);
        r1 = lds128<64>(ra[1]);
      }
      if (tt == 4) {
        load_vec(S3, ra[5]);
        const uint4 v2 = lds128<128>(ra[1]), v3 = lds128<192>(ra[1]);
        S1[8] = v2.x; S1[9] = v2.y; S1[10] = v2.z; S1[11] = v2.w; S1[12] = v3.x; S1[13] = v3.y; S1[14] = v3.z; S1[15] = v3.w;
        S1[0] = r0.x; S1[1] = r0.y; S1[2] = r0.z; S1[3] = r0.w; S1[4] = r1.x; S1[5] = r1.y; S1[6] = r1.z; S1[7] = r1.w;
      }
      sched_fence(ck, never);
      s_chain();
      sched_fence(ck, never);
      epilogue();
      sched_fence(ck, never);
      if (tt == 2 && !rdy) mbar_wait(sbase + OFF_BAR + 8 * min(el + 2, n_c - 1), 0);
      if (tt == 0) { products(S1, S3, S0); bump(ra[3]); }
      if (tt == 1) { products(S1, S0, S2); bump(ra[4]); }
      if (tt == 2) { products(S0, S2, S1); bump(ra[2]); }
      if (tt == 3) products(S1, S2, S3);
      if (tt == 4) {
        products(S0, S1, S3);
        bump(ra[0]); bump(ra[1]); bump(ra[5]);
        asm volatile("add.u32 %0, %0, %1;" : "+r"(pt_ptr) : "n"(2 * ES_STRIDE));
        el += 2;
      }
      sched_fence(ck, never);
      keep2(ck, f0, f1, never);
      if (!last) {
        bar_sync2<4, 5>(wg);
        issue();
      }
    };
#pragma unroll 1
    for (;;) {
      tile(std::integral_constant<int, 0>{});
      tile(std::integral_constant<int, 1>{});
      tile(std::integral_constant<int, 2>{});
      if (left == 0) break;
      tile(std::integral_constant<int, 3>{});
      tile(std::integral_constant<int, 4>{});
      left--;
    }
    tile(std::integral_constant<int, 8 + 3>{});
    auto side = [&]() {
      fold();
      sts32o<3072>(pt_ptr, eh0);
      sts32o<3072 + 512>(pt_ptr, eh1);
      bar_arrive2<10, 11, 160>(wg);
      s_chain();
    };
    bar_sync2<4, 5>(wg);
    uint32_t al[96 / 4], ah[32 / 4];
    fence_regs(Af);
    wgmma_fence();
#pragma unroll
    for (int s = 0; s < 8; s++) {
      const uint64_t d = dB + (uint64_t)(s * (2048 >> 4));
      if (s == 0) wgmma_rs_n96<0>(al, Af[0], Af[1], Af[2], Af[3], d);
      else wgmma_rs_n96<1>(al, Af[4 * s], Af[4 * s + 1], Af[4 * s + 2], Af[4 * s + 3], d);
    }
    wgmma_commit();
    sched_fence(ck, never);
    side();
    sched_fence(ck, never);
    wgmma_fence();
#pragma unroll
    for (int s = 0; s < 8; s++) {
      const uint64_t d = dB + (uint64_t)(s * (2048 >> 4) + ((B_NBLK + (96 - 64) * 2) >> 4));
      if (s == 0) wgmma_rs_n32<0>(ah, Af[0], Af[1], Af[2], Af[3], d);
      else wgmma_rs_n32<1>(ah, Af[4 * s], Af[4 * s + 1], Af[4 * s + 2], Af[4 * s + 3], d);
    }
    wgmma_commit();
    bar_arrive2<5, 4>(wg);
    wgmma_wait<1>();
    fence_regs(al);
    eh0 = hmul2(bias_relu2(al[0], bs[0]), hs[0]);
    eh1 = hmul2(bias_relu2(al[1], bs[0]), hs[0]);
#pragma unroll
    for (int i = 1; i < 96 / 8; i++) {
      eh0 = hfma2(bias_relu2(al[2 * i], bs[i]), hs[i], eh0);
      eh1 = hfma2(bias_relu2(al[2 * i + 1], bs[i]), hs[i], eh1);
    }
    asm volatile("" : "+r"(eh0), "+r"(eh1)::"memory");
    sched_fence(ck, never);
    wgmma_wait<0>();
    fence_regs(ah);
#pragma unroll
    for (int i = 0; i < 32 / 8; i++) {
      eh0 = hfma2(bias_relu2(ah[2 * i], bs[96 / 8 + i]), hs[96 / 8 + i], eh0);
      eh1 = hfma2(bias_relu2(ah[2 * i + 1], bs[96 / 8 + i]), hs[96 / 8 + i], eh1);
    }
    fold();
    sts32o<4096>(pt_ptr + ck, eh0);
    sts32o<4096 + 512>(pt_ptr, eh1);
    bar_arrive2<8, 9, 160>(wg);
    sched_fence(ck, never);
    if (wg == 0) {
      named_bar_sync(4, 256);
    } else if (n_c & 1) {
      for (int i = 0; i < 5; i++) {
        named_bar_sync(5, 256);
        named_bar_arrive(4, 256);
      }
    }
  } else {
    {
      asm volatile("setmaxnreg.dec.sync.aligned.u32 104;");
      uint4 wr[16];
#pragma unroll
      for (int r = 0; r < 16; r++) wr[r] = ldg128(W + (32 * wq + 2 * r) * kD + 8 * lane);
      const uint32_t wa = sbase + OFF_B + ((lane >> 3) & 1) * B_NBLK + wq * 4096 + (lane >> 4) * 128;
      const uint32_t lx = (lane & 7) ^ (lane >> 4);
      uint32_t wad[4], mw = 0;
#pragma unroll
      for (int x = 0; x < 4; x++) wad[x] = wa + ((lx ^ (2 * x)) << 4);
      sched_fence(ck, never);
      static_for<0, 16>([&](auto Rc) {
        constexpr int r = decltype(Rc)::value;
        uint4 v;
        v.x = bf2h_x16(wr[r].x); v.y = bf2h_x16(wr[r].y); v.z = bf2h_x16(wr[r].z); v.w = bf2h_x16(wr[r].w);
        sts128<(r & 3) * 1024 + (r >> 2) * 256>(wad[r >> 2], v);
        mw = babsmax2(babsmax2(mw, wr[r].x), babsmax2(wr[r].y, babsmax2(wr[r].z, wr[r].w)));
        if (r == 3) sched_fence(ck, never);
        if (r == 7 || r == 11) sched_fence(ck, never);
      });
      sched_fence(ck, never);
      fence_proxy_async();
      named_bar_arrive(3, 256);
      sched_fence(ck, never);
      sts32p(sbase + OFF_STAT + wq * 4 + ck, redux_max(absmax_bits(mw)), lane == 0);
    }
    named_bar_sync(15, 128);
    asm volatile("setmaxnreg.dec.sync.aligned.u32 %0;" ::"n"(504 - 2 * 216));
    if ((int)blockIdx.x >= n_left) helper_rest(idx, table, W, late, per, n_elem, n_left, smem);
    else {
      named_bar_sync(6, 160);
#pragma unroll 1
      for (int q = 2; q < 8; q++) {
        const int e = min((int)blockIdx.x * 256 + (t >> 2) * 8 + q, n_elem - 1);
        const uint32_t row = ldg32(idx + e * kF + (t & 3));
        asm volatile("prefetch.global.L2 [%0];\nprefetch.global.L2 [%0+128];" ::"l"(table + (size_t)row * kD) : "memory");
      }
    }
  }
}

}

extern "C" void kernel_launch(void* const* d_in, const int* in_sizes, int n_in, void* d_out, int out_size) {
  const int* idx = (const int*)d_in[0];
  const __nv_bfloat16* table = (const __nv_bfloat16*)d_in[1];
  const int* ii = (const int*)d_in[2];
  const int* jj = (const int*)d_in[3];
  const __nv_bfloat16* W = (const __nv_bfloat16*)d_in[4];
  const __nv_bfloat16* bias = (const __nv_bfloat16*)d_in[5];
  const __nv_bfloat16* hvec = (const __nv_bfloat16*)d_in[6];
  const __nv_bfloat16* pvec = (const __nv_bfloat16*)d_in[7];
  __nv_bfloat16* out = (__nv_bfloat16*)d_out;
  const int B = out_size;

  static int num_sms = 0;
  if (num_sms == 0) {
    int dev = 0;
    cudaGetDevice(&dev);
    cudaDeviceGetAttribute(&num_sms, cudaDevAttrMultiProcessorCount, dev);
    cudaFuncSetAttribute(afm_kernel, cudaFuncAttributeMaxDynamicSharedMemorySize, SMEM_BYTES);
  }
  const Sched sched = {{
    0x2d2cb011u, 0x2c9a0662u, 0x2876c228u, 0x26074141u, 0x2655c878u, 0x2985dc43u, 0x18722403u, 0x22299aaeu,
    0x02a6b0b1u, 0x30d73d00u, 0x00941af1u, 0x2ee29c4au, 0x2ad5a410u, 0x21250923u, 0x328a84aeu, 0x0d780599u,
    0x324551f8u, 0x3112a583u, 0x062ca4eeu, 0x155360e3u, 0x1cb204d6u, 0x1f4280c9u, 0x2776e487u, 0x090b60a2u,
    0x2413bf17u, 0x168b28ecu, 0x10c78a70u, 0x2f578ed1u, 0x1a334ac2u, 0x0888c875u, 0x1d5a3249u, 0x2305bf2au
  }};
  for (int off = 0; off < B; off += kMaxChunk) {
    const int n = B - off < kMaxChunk ? B - off : kMaxChunk;
    const int n_left = (n + 255) / 256;
    const int room = num_sms - n_left > 1 ? num_sms - n_left : 1;
    int per = (n + room - 1) / room;
    if (per > kMaxB) per = kMaxB;
    const int n_main = (n + per - 1) / per;
    const Late late = {{bias, hvec, pvec, pvec}, ii, jj, out + off, sched};
    afm_kernel<<<n_left + n_main, kThreads, SMEM_BYTES>>>(idx + (size_t)off * kF, table, W, per * kF * 4, n_left * per * kF * 4,
                                                          (n * kF - 2) * 4, per, n, n_left, late);
  }
}
```
